```python
import torch

def _softmax(x, axis=-1):
    return torch.softmax(x, dim=axis)
def _gelu(x):
    return torch.nn.functional.gelu(x, approximate="tanh")
def _silu(x):
    return torch.nn.functional.silu(x)
def _sigmoid(x):
    return torch.sigmoid(x)
def _layernorm(x, axis=-1, eps=1e-5):
    m = x.mean(dim=axis, keepdim=True)
    v = x.var(dim=axis, keepdim=True, unbiased=False)
    return (x - m) / torch.sqrt(v + eps)
def _scatter_add(tgt, idx, src, axis=0):
    return tgt.clone().index_add_(axis, idx, src)
def _segment_sum(src, seg, n):
    out = torch.zeros((n,) + src.shape[1:], dtype=src.dtype)
    return out.index_add_(0, seg, src)
def _pad(x, pw):
    flat = tuple(v for pair in reversed(pw) for v in pair)
    return torch.nn.functional.pad(x, flat)

kernel_name = 'recurrent_scan__ssm_conv_s5__glu_gated_bilinear__prompt'

def setup_inputs():

    _w = (lambda a: (lambda t: t.to(torch.bfloat16) if t.is_floating_point() else t)(torch.as_tensor(a)))
    def _A_setup():
        B, S, D = 1, 2048, 576
        P = D
        Lambda_re = -0.5 * (lambda _x: torch.exp(torch.as_tensor(_x)))((lambda *s: torch.randn(*s, dtype=torch.bfloat16) * 0.8)(P))
        Lambda_im = (lambda *s: torch.randn(*s, dtype=torch.bfloat16) * 0.8)(P) * 1.0
        B_re = (lambda *s: torch.randn(*s, dtype=torch.bfloat16) * 1.6)(P, D) * (D ** -0.5)
        B_im = (lambda *s: torch.randn(*s, dtype=torch.bfloat16) * 1.6)(P, D) * (D ** -0.5)
        C_re = (lambda *s: torch.randn(*s, dtype=torch.bfloat16) * 1.6)(D, P) * (P ** -0.5)
        C_im = (lambda *s: torch.randn(*s, dtype=torch.bfloat16) * 1.6)(D, P) * (P ** -0.5)
        log_dt = (lambda *s: torch.randn(*s, dtype=torch.bfloat16) * 0.8)(P) * 0.3 - 2.0
        Dskip = (lambda *s: torch.randn(*s, dtype=torch.bfloat16) * 0.8)(D)
        return {
            "x": _w((lambda *s: torch.randn(*s, dtype=torch.bfloat16) * 0.05)(B, S, D)),
            "Lambda_re": _w(Lambda_re),
            "Lambda_im": _w(Lambda_im),
            "B_re": _w(B_re),
            "B_im": _w(B_im),
            "C_re": _w(C_re),
            "C_im": _w(C_im),
            "log_dt": _w(log_dt),
            "Dskip": _w(Dskip),
        }
    _A_in = _A_setup()

    def _B_setup():
        B, S, D, F = 1, 2048, 576, 4608
        return {
            "x": _w((lambda *s: torch.randn(*s, dtype=torch.bfloat16) * 0.05)(B, S, D)),
            "w_gate": _w((lambda *s: torch.randn(*s, dtype=torch.bfloat16) * 0.2)(D, F) * (D ** -0.5)),
            "w_up": _w((lambda *s: torch.randn(*s, dtype=torch.bfloat16) * 0.2)(D, F) * (D ** -0.5)),
            "w_down": _w((lambda *s: torch.randn(*s, dtype=torch.bfloat16) * 0.2)(F, D) * (F ** -0.5)),
        }
    _B_in = _B_setup()

    return {
        "A_x": _A_in["x"],
        "A_Lambda_re": _A_in["Lambda_re"],
        "A_Lambda_im": _A_in["Lambda_im"],
        "A_B_re": _A_in["B_re"],
        "A_B_im": _A_in["B_im"],
        "A_C_re": _A_in["C_re"],
        "A_C_im": _A_in["C_im"],
        "A_log_dt": _A_in["log_dt"],
        "A_Dskip": _A_in["Dskip"],
        "B_x": _B_in["x"],
        "B_w_gate": _B_in["w_gate"],
        "B_w_up": _B_in["w_up"],
        "B_w_down": _B_in["w_down"],
    }

def reference(A_x, A_Lambda_re, A_Lambda_im, A_B_re, A_B_im, A_C_re, A_C_im, A_log_dt, A_Dskip, B_x, B_w_gate, B_w_up, B_w_down):
    def _A_ref(x, Lambda_re, Lambda_im, B_re, B_im, C_re, C_im, log_dt, Dskip):
        Bsz, L, H = x.shape
        Lam = Lambda_re + 1j * Lambda_im
        Bmat = B_re + 1j * B_im
        Cmat = C_re + 1j * C_im
        dt = torch.exp(log_dt)
        Lam_bar = torch.exp(dt * Lam)
        B_bar = ((Lam_bar - 1.0) / Lam)[:, None] * Bmat
        Bu = torch.einsum("bld,pd->blp", x + 0j, B_bar)
        h = torch.zeros_like(Bu[:, 0, :])
        hs = []
        for t in range(L):
            h = Lam_bar[None, :] * h + Bu[:, t, :]
            hs.append(h)
        hseq = torch.stack(hs, 1)
        y = 2.0 * torch.einsum("blp,dp->bld", hseq, Cmat).real + x * Dskip[None, None, :]
        return y

    def _B_ref(x, w_gate, w_up, w_down):
        g = torch.einsum("bsd,df->bsf", x, w_gate)
        u = torch.einsum("bsd,df->bsf", x, w_up)
        h = g * u
        return torch.einsum("bsf,fd->bsd", h, w_down)

    x = A_x
    xn = _layernorm(x, axis=-1)
    s = _A_ref(xn, A_Lambda_re, A_Lambda_im, A_B_re, A_B_im, A_C_re, A_C_im, A_log_dt, A_Dskip)
    g = _silu(_B_ref(xn, B_w_gate, B_w_up, B_w_down))
    return x + s * g
```

```cpp
#include <cuda_runtime.h>
#include <cuda.h>
#include <cuda_bf16.h>
#include <stdint.h>

#define DEVI __device__ __forceinline__
template<int TA,int TB,uint32_t OA,uint32_t OB> DEVI void wg_ss64(float (&d)[32], uint64_t da, uint64_t db) {
  asm volatile("{\n.reg .pred p;\n.reg .b64 x,y;\nsetp.eq.b32 p,1,1;\nadd.s64 x,%32,%36;\nadd.s64 y,%33,%37;\n"
    "wgmma.mma_async.sync.aligned.m64n64k16.f32.bf16.bf16 "
    "{%0,%1,%2,%3,%4,%5,%6,%7,%8,%9,%10,%11,%12,%13,%14,%15,%16,%17,%18,%19,%20,%21,%22,%23,%24,%25,%26,%27,%28,%29,%30,%31},x,y,p,1,1,%34,%35;\n}\n"
    : "+f"(d[0]),"+f"(d[1]),"+f"(d[2]),"+f"(d[3]),"+f"(d[4]),"+f"(d[5]),"+f"(d[6]),"+f"(d[7]),"+f"(d[8]),"+f"(d[9]),"+f"(d[10]),"+f"(d[11]),"+f"(d[12]),"+f"(d[13]),"+f"(d[14]),"+f"(d[15]),"+f"(d[16]),"+f"(d[17]),"+f"(d[18]),"+f"(d[19]),"+f"(d[20]),"+f"(d[21]),"+f"(d[22]),"+f"(d[23]),"+f"(d[24]),"+f"(d[25]),"+f"(d[26]),"+f"(d[27]),"+f"(d[28]),"+f"(d[29]),"+f"(d[30]),"+f"(d[31])
    : "l"(da),"l"(db),"n"(TA),"n"(TB),"n"(OA),"n"(OB));
}
template<int TA,int TB,uint32_t OA,uint32_t OB> DEVI void wg_ss64p(float (&d)[32], uint64_t da, uint64_t db, int f) {
  asm volatile("{\n.reg .pred p;\n.reg .b64 x,y;\nsetp.ne.b32 p,%38,0;\nadd.s64 x,%32,%36;\nadd.s64 y,%33,%37;\n"
    "wgmma.mma_async.sync.aligned.m64n64k16.f32.bf16.bf16 "
    "{%0,%1,%2,%3,%4,%5,%6,%7,%8,%9,%10,%11,%12,%13,%14,%15,%16,%17,%18,%19,%20,%21,%22,%23,%24,%25,%26,%27,%28,%29,%30,%31},x,y,p,1,1,%34,%35;\n}\n"
    : "+f"(d[0]),"+f"(d[1]),"+f"(d[2]),"+f"(d[3]),"+f"(d[4]),"+f"(d[5]),"+f"(d[6]),"+f"(d[7]),"+f"(d[8]),"+f"(d[9]),"+f"(d[10]),"+f"(d[11]),"+f"(d[12]),"+f"(d[13]),"+f"(d[14]),"+f"(d[15]),"+f"(d[16]),"+f"(d[17]),"+f"(d[18]),"+f"(d[19]),"+f"(d[20]),"+f"(d[21]),"+f"(d[22]),"+f"(d[23]),"+f"(d[24]),"+f"(d[25]),"+f"(d[26]),"+f"(d[27]),"+f"(d[28]),"+f"(d[29]),"+f"(d[30]),"+f"(d[31])
    : "l"(da),"l"(db),"n"(TA),"n"(TB),"n"(OA),"n"(OB),"r"(f));
}
template<int TA,int TB,uint32_t OA,uint32_t OB> DEVI void wg_ss128(float (&d)[64], uint64_t da, uint64_t db) {
  asm volatile("{\n.reg .pred p;\n.reg .b64 x,y;\nsetp.eq.b32 p,1,1;\nadd.s64 x,%64,%68;\nadd.s64 y,%65,%69;\n"
    "wgmma.mma_async.sync.aligned.m64n128k16.f32.bf16.bf16 "
    "{%0,%1,%2,%3,%4,%5,%6,%7,%8,%9,%10,%11,%12,%13,%14,%15,%16,%17,%18,%19,%20,%21,%22,%23,%24,%25,%26,%27,%28,%29,%30,%31,%32,%33,%34,%35,%36,%37,%38,%39,%40,%41,%42,%43,%44,%45,%46,%47,%48,%49,%50,%51,%52,%53,%54,%55,%56,%57,%58,%59,%60,%61,%62,%63},x,y,p,1,1,%66,%67;\n}\n"
    : "+f"(d[0]),"+f"(d[1]),"+f"(d[2]),"+f"(d[3]),"+f"(d[4]),"+f"(d[5]),"+f"(d[6]),"+f"(d[7]),"+f"(d[8]),"+f"(d[9]),"+f"(d[10]),"+f"(d[11]),"+f"(d[12]),"+f"(d[13]),"+f"(d[14]),"+f"(d[15]),"+f"(d[16]),"+f"(d[17]),"+f"(d[18]),"+f"(d[19]),"+f"(d[20]),"+f"(d[21]),"+f"(d[22]),"+f"(d[23]),"+f"(d[24]),"+f"(d[25]),"+f"(d[26]),"+f"(d[27]),"+f"(d[28]),"+f"(d[29]),"+f"(d[30]),"+f"(d[31]),"+f"(d[32]),"+f"(d[33]),"+f"(d[34]),"+f"(d[35]),"+f"(d[36]),"+f"(d[37]),"+f"(d[38]),"+f"(d[39]),"+f"(d[40]),"+f"(d[41]),"+f"(d[42]),"+f"(d[43]),"+f"(d[44]),"+f"(d[45]),"+f"(d[46]),"+f"(d[47]),"+f"(d[48]),"+f"(d[49]),"+f"(d[50]),"+f"(d[51]),"+f"(d[52]),"+f"(d[53]),"+f"(d[54]),"+f"(d[55]),"+f"(d[56]),"+f"(d[57]),"+f"(d[58]),"+f"(d[59]),"+f"(d[60]),"+f"(d[61]),"+f"(d[62]),"+f"(d[63])
    : "l"(da),"l"(db),"n"(TA),"n"(TB),"n"(OA),"n"(OB));
}
template<int TA,int TB,uint32_t OA,uint32_t OB> DEVI void wg_ss128p(float (&d)[64], uint64_t da, uint64_t db, int f) {
  asm volatile("{\n.reg .pred p;\n.reg .b64 x,y;\nsetp.ne.b32 p,%70,0;\nadd.s64 x,%64,%68;\nadd.s64 y,%65,%69;\n"
    "wgmma.mma_async.sync.aligned.m64n128k16.f32.bf16.bf16 "
    "{%0,%1,%2,%3,%4,%5,%6,%7,%8,%9,%10,%11,%12,%13,%14,%15,%16,%17,%18,%19,%20,%21,%22,%23,%24,%25,%26,%27,%28,%29,%30,%31,%32,%33,%34,%35,%36,%37,%38,%39,%40,%41,%42,%43,%44,%45,%46,%47,%48,%49,%50,%51,%52,%53,%54,%55,%56,%57,%58,%59,%60,%61,%62,%63},x,y,p,1,1,%66,%67;\n}\n"
    : "+f"(d[0]),"+f"(d[1]),"+f"(d[2]),"+f"(d[3]),"+f"(d[4]),"+f"(d[5]),"+f"(d[6]),"+f"(d[7]),"+f"(d[8]),"+f"(d[9]),"+f"(d[10]),"+f"(d[11]),"+f"(d[12]),"+f"(d[13]),"+f"(d[14]),"+f"(d[15]),"+f"(d[16]),"+f"(d[17]),"+f"(d[18]),"+f"(d[19]),"+f"(d[20]),"+f"(d[21]),"+f"(d[22]),"+f"(d[23]),"+f"(d[24]),"+f"(d[25]),"+f"(d[26]),"+f"(d[27]),"+f"(d[28]),"+f"(d[29]),"+f"(d[30]),"+f"(d[31]),"+f"(d[32]),"+f"(d[33]),"+f"(d[34]),"+f"(d[35]),"+f"(d[36]),"+f"(d[37]),"+f"(d[38]),"+f"(d[39]),"+f"(d[40]),"+f"(d[41]),"+f"(d[42]),"+f"(d[43]),"+f"(d[44]),"+f"(d[45]),"+f"(d[46]),"+f"(d[47]),"+f"(d[48]),"+f"(d[49]),"+f"(d[50]),"+f"(d[51]),"+f"(d[52]),"+f"(d[53]),"+f"(d[54]),"+f"(d[55]),"+f"(d[56]),"+f"(d[57]),"+f"(d[58]),"+f"(d[59]),"+f"(d[60]),"+f"(d[61]),"+f"(d[62]),"+f"(d[63])
    : "l"(da),"l"(db),"n"(TA),"n"(TB),"n"(OA),"n"(OB),"r"(f));
}
template<int TB,uint32_t OB> DEVI void wg_rs64(float (&d)[32], const uint32_t* a, uint64_t db) {
  asm volatile("{\n.reg .pred p;\n.reg .b64 y;\nsetp.eq.b32 p,1,1;\nadd.s64 y,%36,%38;\n"
    "wgmma.mma_async.sync.aligned.m64n64k16.f32.bf16.bf16 "
    "{%0,%1,%2,%3,%4,%5,%6,%7,%8,%9,%10,%11,%12,%13,%14,%15,%16,%17,%18,%19,%20,%21,%22,%23,%24,%25,%26,%27,%28,%29,%30,%31},{%32,%33,%34,%35},y,p,1,1,%37;\n}\n"
    : "+f"(d[0]),"+f"(d[1]),"+f"(d[2]),"+f"(d[3]),"+f"(d[4]),"+f"(d[5]),"+f"(d[6]),"+f"(d[7]),"+f"(d[8]),"+f"(d[9]),"+f"(d[10]),"+f"(d[11]),"+f"(d[12]),"+f"(d[13]),"+f"(d[14]),"+f"(d[15]),"+f"(d[16]),"+f"(d[17]),"+f"(d[18]),"+f"(d[19]),"+f"(d[20]),"+f"(d[21]),"+f"(d[22]),"+f"(d[23]),"+f"(d[24]),"+f"(d[25]),"+f"(d[26]),"+f"(d[27]),"+f"(d[28]),"+f"(d[29]),"+f"(d[30]),"+f"(d[31])
    : "r"(a[0]),"r"(a[1]),"r"(a[2]),"r"(a[3]),"l"(db),"n"(TB),"n"(OB));
}
template<int TB,uint32_t OB> DEVI void wg_rs64z(float (&d)[32], const uint32_t* a, uint64_t db) {
  asm volatile("{\n.reg .pred p;\n.reg .b64 y;\nsetp.ne.b32 p,1,1;\nadd.s64 y,%36,%38;\n"
    "wgmma.mma_async.sync.aligned.m64n64k16.f32.bf16.bf16 "
    "{%0,%1,%2,%3,%4,%5,%6,%7,%8,%9,%10,%11,%12,%13,%14,%15,%16,%17,%18,%19,%20,%21,%22,%23,%24,%25,%26,%27,%28,%29,%30,%31},{%32,%33,%34,%35},y,p,1,1,%37;\n}\n"
    : "=f"(d[0]),"=f"(d[1]),"=f"(d[2]),"=f"(d[3]),"=f"(d[4]),"=f"(d[5]),"=f"(d[6]),"=f"(d[7]),"=f"(d[8]),"=f"(d[9]),"=f"(d[10]),"=f"(d[11]),"=f"(d[12]),"=f"(d[13]),"=f"(d[14]),"=f"(d[15]),"=f"(d[16]),"=f"(d[17]),"=f"(d[18]),"=f"(d[19]),"=f"(d[20]),"=f"(d[21]),"=f"(d[22]),"=f"(d[23]),"=f"(d[24]),"=f"(d[25]),"=f"(d[26]),"=f"(d[27]),"=f"(d[28]),"=f"(d[29]),"=f"(d[30]),"=f"(d[31])
    : "r"(a[0]),"r"(a[1]),"r"(a[2]),"r"(a[3]),"l"(db),"n"(TB),"n"(OB));
}
template<int TB,uint32_t OB> DEVI void wg_rs128(float (&d)[64], const uint32_t* a, uint64_t db) {
  asm volatile("{\n.reg .pred p;\n.reg .b64 y;\nsetp.eq.b32 p,1,1;\nadd.s64 y,%68,%70;\n"
    "wgmma.mma_async.sync.aligned.m64n128k16.f32.bf16.bf16 "
    "{%0,%1,%2,%3,%4,%5,%6,%7,%8,%9,%10,%11,%12,%13,%14,%15,%16,%17,%18,%19,%20,%21,%22,%23,%24,%25,%26,%27,%28,%29,%30,%31,%32,%33,%34,%35,%36,%37,%38,%39,%40,%41,%42,%43,%44,%45,%46,%47,%48,%49,%50,%51,%52,%53,%54,%55,%56,%57,%58,%59,%60,%61,%62,%63},{%64,%65,%66,%67},y,p,1,1,%69;\n}\n"
    : "+f"(d[0]),"+f"(d[1]),"+f"(d[2]),"+f"(d[3]),"+f"(d[4]),"+f"(d[5]),"+f"(d[6]),"+f"(d[7]),"+f"(d[8]),"+f"(d[9]),"+f"(d[10]),"+f"(d[11]),"+f"(d[12]),"+f"(d[13]),"+f"(d[14]),"+f"(d[15]),"+f"(d[16]),"+f"(d[17]),"+f"(d[18]),"+f"(d[19]),"+f"(d[20]),"+f"(d[21]),"+f"(d[22]),"+f"(d[23]),"+f"(d[24]),"+f"(d[25]),"+f"(d[26]),"+f"(d[27]),"+f"(d[28]),"+f"(d[29]),"+f"(d[30]),"+f"(d[31]),"+f"(d[32]),"+f"(d[33]),"+f"(d[34]),"+f"(d[35]),"+f"(d[36]),"+f"(d[37]),"+f"(d[38]),"+f"(d[39]),"+f"(d[40]),"+f"(d[41]),"+f"(d[42]),"+f"(d[43]),"+f"(d[44]),"+f"(d[45]),"+f"(d[46]),"+f"(d[47]),"+f"(d[48]),"+f"(d[49]),"+f"(d[50]),"+f"(d[51]),"+f"(d[52]),"+f"(d[53]),"+f"(d[54]),"+f"(d[55]),"+f"(d[56]),"+f"(d[57]),"+f"(d[58]),"+f"(d[59]),"+f"(d[60]),"+f"(d[61]),"+f"(d[62]),"+f"(d[63])
    : "r"(a[0]),"r"(a[1]),"r"(a[2]),"r"(a[3]),"l"(db),"n"(TB),"n"(OB));
}
template<int TB,uint32_t OB> DEVI void wg_rs128z(float (&d)[64], const uint32_t* a, uint64_t db) {
  asm volatile("{\n.reg .pred p;\n.reg .b64 y;\nsetp.ne.b32 p,1,1;\nadd.s64 y,%68,%70;\n"
    "wgmma.mma_async.sync.aligned.m64n128k16.f32.bf16.bf16 "
    "{%0,%1,%2,%3,%4,%5,%6,%7,%8,%9,%10,%11,%12,%13,%14,%15,%16,%17,%18,%19,%20,%21,%22,%23,%24,%25,%26,%27,%28,%29,%30,%31,%32,%33,%34,%35,%36,%37,%38,%39,%40,%41,%42,%43,%44,%45,%46,%47,%48,%49,%50,%51,%52,%53,%54,%55,%56,%57,%58,%59,%60,%61,%62,%63},{%64,%65,%66,%67},y,p,1,1,%69;\n}\n"
    : "=f"(d[0]),"=f"(d[1]),"=f"(d[2]),"=f"(d[3]),"=f"(d[4]),"=f"(d[5]),"=f"(d[6]),"=f"(d[7]),"=f"(d[8]),"=f"(d[9]),"=f"(d[10]),"=f"(d[11]),"=f"(d[12]),"=f"(d[13]),"=f"(d[14]),"=f"(d[15]),"=f"(d[16]),"=f"(d[17]),"=f"(d[18]),"=f"(d[19]),"=f"(d[20]),"=f"(d[21]),"=f"(d[22]),"=f"(d[23]),"=f"(d[24]),"=f"(d[25]),"=f"(d[26]),"=f"(d[27]),"=f"(d[28]),"=f"(d[29]),"=f"(d[30]),"=f"(d[31]),"=f"(d[32]),"=f"(d[33]),"=f"(d[34]),"=f"(d[35]),"=f"(d[36]),"=f"(d[37]),"=f"(d[38]),"=f"(d[39]),"=f"(d[40]),"=f"(d[41]),"=f"(d[42]),"=f"(d[43]),"=f"(d[44]),"=f"(d[45]),"=f"(d[46]),"=f"(d[47]),"=f"(d[48]),"=f"(d[49]),"=f"(d[50]),"=f"(d[51]),"=f"(d[52]),"=f"(d[53]),"=f"(d[54]),"=f"(d[55]),"=f"(d[56]),"=f"(d[57]),"=f"(d[58]),"=f"(d[59]),"=f"(d[60]),"=f"(d[61]),"=f"(d[62]),"=f"(d[63])
    : "r"(a[0]),"r"(a[1]),"r"(a[2]),"r"(a[3]),"l"(db),"n"(TB),"n"(OB));
}

constexpr int SEQ = 2048, DM = 576, FF = 4608;
constexpr uint32_t SLOT = 16384;
constexpr uint32_t OFF_BAR = 14 * SLOT;
constexpr uint32_t OFF_PAR = OFF_BAR + 512;
constexpr uint32_t SMEM_BYTES = OFF_PAR + 1024;
constexpr int B_FULL = 0, B_FULLT = 5, B_XT = 13, B_DF = 15, B_Z = 19, B_RES = 21, B_G0 = 22, B_G1 = 23,
              B_EMPTY = 24, B_EMPTYT = 29, B_XN = 37, B_HS = 44, B_DR = 46, B_X0 = 48;
constexpr uint32_t SPIN_MAX = 400000;

struct alignas(64) Params {
  CUtensorMap wg, wu, wd, bre, bim, cre, cim, hs, xp;
  const __nv_bfloat16 *x, *lre, *lim, *ldt, *dskip, *pw[7];
  float* out;
  uint64_t desc;
};

__device__ __align__(1024) uint4 g_hsT[1152 * SEQ / 8];
__device__ __align__(1024) uint4 g_xn[16 * 9 * 1024];
__device__ __align__(1024) uint4 g_z[16 * 9 * 1024];
__device__ __align__(1024) float4 g_state[9 * 32 * 32];
__device__ __align__(1024) float4 g_y8[16 * 8 * 8 * 32];
constexpr int SY_EPOCH = 0, SY_XN = 160, SY_HS = SY_XN + 16 * 32, SY_Z = SY_HS + 32 * 32;
__device__ __align__(1024) uint32_t g_sync[SY_Z + 32 * 32];
#define TR(role, idx)
#define TRC(idx)

DEVI uint32_t smem_u32(const void* p) { return (uint32_t)__cvta_generic_to_shared(p); }
DEVI void mbar_init(uint32_t bar, uint32_t cnt) { asm volatile("mbarrier.init.shared::cta.b64 [%0], %1;" :: "r"(bar), "r"(cnt)); }
DEVI void mbar_expect(uint32_t bar, uint32_t bytes) { asm volatile("mbarrier.arrive.expect_tx.shared::cta.b64 _, [%0], %1;" :: "r"(bar), "r"(bytes) : "memory"); }
DEVI void mbar_arrive(uint32_t bar) { asm volatile("mbarrier.arrive.shared::cta.b64 _, [%0];" :: "r"(bar) : "memory"); }
DEVI void mbar_arrive_warp(uint32_t bar) {
  asm volatile("{\n.reg .pred p;\nelect.sync _|p, 0xffffffff;\n@p mbarrier.arrive.shared::cta.b64 _, [%0];\n}" :: "r"(bar) : "memory");
}
DEVI void mbar_arrive_warp_if(uint32_t bar, int f) {
  asm volatile("{\n.reg .pred p, q;\nelect.sync _|p, 0xffffffff;\nsetp.ne.and.b32 q, %1, 0, p;\n@q mbarrier.arrive.shared::cta.b64 _, [%0];\n}" :: "r"(bar), "r"(f) : "memory");
}
DEVI void mbar_wait(uint32_t& c, uint32_t bar, uint32_t parity) {
  asm volatile("{\n.reg .pred p, q;\nLW:\nadd.u32 %0, %0, 1;\nsetp.lt.u32 q, %0, %3;\n"
               "mbarrier.try_wait.parity.shared::cta.b64 p, [%1], %2;\nnot.pred p, p;\nand.pred p, p, q;\n@p bra LW;\n}"
               : "+&r"(c) : "r"(bar), "r"(parity), "n"(SPIN_MAX) : "memory");
}
DEVI void spin_check(uint32_t c) { asm volatile("{\n.reg .pred p;\nsetp.ge.u32 p, %0, %1;\n@p trap;\n}" :: "r"(c), "n"(SPIN_MAX)); }
DEVI bool elect() { uint32_t p; asm volatile("{\n.reg .pred p;\nelect.sync _|p, 0xffffffff;\nselp.u32 %0, 1, 0, p;\n}" : "=r"(p)); return p; }
DEVI void poll_ge(const uint32_t* p, uint32_t target) {
  asm volatile("{\n.reg .pred p;\n.reg .u32 c, v;\nmov.u32 c, 0;\nLW:\n"
               "ld.acquire.gpu.global.u32 v, [%0];\nsub.u32 v, v, %1;\nsetp.ge.s32 p, v, 0;\n@p bra LD;\n"
               "nanosleep.u32 40;\nadd.u32 c, c, 1;\nsetp.gt.u32 p, c, 2000000;\n@p trap;\nbra LW;\nLD:\n}" :: "l"(p), "r"(target) : "memory");
}
DEVI void fence_gpu() { asm volatile("fence.acq_rel.gpu;" ::: "memory"); }
DEVI void fence_async_all() { asm volatile("fence.proxy.async;" ::: "memory"); }
DEVI void fence_async_smem() { asm volatile("fence.proxy.async.shared::cta;" ::: "memory"); }
DEVI void red_inc(uint32_t* p) { asm volatile("red.relaxed.gpu.global.add.u32 [%0], 1;" :: "l"(p) : "memory"); }
DEVI void st_relaxed(uint32_t* p, uint32_t v) { asm volatile("st.relaxed.gpu.global.u32 [%0], %1;" :: "l"(p), "r"(v) : "memory"); }
DEVI uint32_t ld_relaxed(const uint32_t* p) { uint32_t v; asm volatile("ld.relaxed.gpu.global.u32 %0, [%1];" : "=r"(v) : "l"(p) : "memory"); return v; }
DEVI void tma2d(uint32_t dst, const CUtensorMap* m, uint32_t bar, int c0, int c1) {
  asm volatile("cp.async.bulk.tensor.2d.shared::cluster.global.mbarrier::complete_tx::bytes [%0], [%1, {%3, %4}], [%2];"
               :: "r"(dst), "l"(m), "r"(bar), "r"(c0), "r"(c1) : "memory");
}
DEVI void tma_x(uint32_t dst, const CUtensorMap* m, uint32_t bar, int col, int seg) {
  asm volatile("cp.async.bulk.tensor.5d.shared::cluster.global.mbarrier::complete_tx::bytes [%0], [%1, {%3, %5, %5, %5, %4}], [%2];"
               :: "r"(dst), "l"(m), "r"(bar), "r"(col), "r"(seg), "r"(0) : "memory");
}
DEVI void pf_l2(const void* p, uint32_t bytes) { asm volatile("cp.async.bulk.prefetch.L2.global [%0], %1;" :: "l"(p), "r"(bytes) : "memory"); }
DEVI void bulk_ld(uint32_t dst, const void* src, uint32_t bytes, uint32_t bar) {
  asm volatile("cp.async.bulk.shared::cluster.global.mbarrier::complete_tx::bytes [%0], [%1], %2, [%3];" :: "r"(dst), "l"(src), "r"(bytes), "r"(bar) : "memory");
}
DEVI void bulk_st(void* dst, uint32_t src, uint32_t bytes) {
  asm volatile("cp.async.bulk.global.shared::cta.bulk_group [%0], [%1], %2;" :: "l"(dst), "r"(src), "r"(bytes) : "memory");
}
DEVI void bulk_red(void* dst, uint32_t src, uint32_t bytes) {
  asm volatile("cp.reduce.async.bulk.global.shared::cta.bulk_group.add.noftz.bf16 [%0], [%1], %2;" :: "l"(dst), "r"(src), "r"(bytes) : "memory");
}
DEVI void wg_fence() { asm volatile("wgmma.fence.sync.aligned;" ::: "memory"); }
DEVI void mbar_wait_f(uint32_t& c, uint32_t bar, uint32_t parity) { mbar_wait(c, bar, parity); wg_fence(); }
DEVI void wg_commit() { asm volatile("wgmma.commit_group.sync.aligned;" ::: "memory"); }
template <int N> DEVI void wg_wait() { asm volatile("wgmma.wait_group.sync.aligned %0;" :: "n"(N) : "memory"); }
template <int N> DEVI void pin(float (&a)[N]) {
#pragma unroll
  for (int i = 0; i < N; i++) asm volatile("" : "+f"(a[i]) :: "memory");
}
template <int N> DEVI void pinu(uint32_t (&a)[N]) {
#pragma unroll
  for (int i = 0; i < N; i++) asm volatile("" : "+r"(a[i]) :: "memory");
}
constexpr uint64_t DESC0 = (512ull << 16) | (0x40000040ull << 32);
DEVI uint32_t pack2(float lo, float hi) { uint32_t r; asm("cvt.rn.bf16x2.f32 %0, %1, %2;" : "=r"(r) : "f"(hi), "f"(lo)); return r; }
DEVI uint32_t hmul2(uint32_t a, uint32_t b) { uint32_t r; asm("mul.rn.bf16x2 %0, %1, %2;" : "=r"(r) : "r"(a), "r"(b)); return r; }
DEVI uint32_t hsub2(uint32_t a, uint32_t b) { uint32_t r; asm("sub.rn.bf16x2 %0, %1, %2;" : "=r"(r) : "r"(a), "r"(b)); return r; }
DEVI uint32_t hfma2(uint32_t a, uint32_t b, uint32_t c) { uint32_t r; asm("fma.rn.bf16x2 %0, %1, %2, %3;" : "=r"(r) : "r"(a), "r"(b), "r"(c)); return r; }
DEVI float blo(uint32_t v) { return __uint_as_float(v << 16); }
DEVI float bhi(uint32_t v) { return __uint_as_float(v & 0xffff0000u); }
DEVI float bround(float f) { return __bfloat162float(__float2bfloat16_rn(f)); }
DEVI void mma16816(float (&d)[4], uint32_t a0, uint32_t a1, uint32_t a2, uint32_t a3, uint32_t b0, uint32_t b1) {
  asm volatile("mma.sync.aligned.m16n8k16.row.col.f32.bf16.bf16.f32 {%0,%1,%2,%3}, {%4,%5,%6,%7}, {%8,%9}, {%0,%1,%2,%3};"
               : "+f"(d[0]), "+f"(d[1]), "+f"(d[2]), "+f"(d[3]) : "r"(a0), "r"(a1), "r"(a2), "r"(a3), "r"(b0), "r"(b1));
}
DEVI void ldsm4(uint32_t* r, uint32_t addr) {
  asm volatile("ldmatrix.sync.aligned.m8n8.x4.shared.b16 {%0,%1,%2,%3}, [%4];" : "=r"(r[0]), "=r"(r[1]), "=r"(r[2]), "=r"(r[3]) : "r"(addr) : "memory");
}
DEVI void stsm4(uint32_t addr, const uint32_t* r) {
  asm volatile("stmatrix.sync.aligned.m8n8.x4.shared.b16 [%4], {%0,%1,%2,%3};" :: "r"(r[0]), "r"(r[1]), "r"(r[2]), "r"(r[3]), "r"(addr) : "memory");
}
template <int I> struct IC { static constexpr int v = I; };
template <int I, int N, class Fn> DEVI void sfor(Fn&& f) { if constexpr (I < N) { f(IC<I>{}); sfor<I + 1, N>(f); } }

struct Scan {
  float lr[2], li[2];
  float cr[2], ci[2];
  float pr[2], pi[2];
  float hr[2], hi[2];
};
constexpr int W_Q = 0, W_F = 4, W_G = 8, W_L = 16;
DEVI float uf(uint32_t v) { return __uint_as_float(v); }
DEVI uint32_t fu(float v) { return __float_as_uint(v); }
DEVI void csq(float& r, float& i) { float t = r * i; r = fmaf(r, r, -i * i); i = t + t; }
DEVI void cmul(float& r, float& i, float ar, float ai) { float t = fmaf(r, ar, -i * ai); i = fmaf(r, ai, i * ar); r = t; }

DEVI void scan_params(uint32_t dst, float a, float b, float ldt) {
  const float dt = bround(expf(ldt));
  const float e = expf(dt * a);
  float sn, cs; sincosf(dt * b, &sn, &cs);
  const float lr = e * cs, li = e * sn, nr = lr - 1.0f;
  const bool sw = fabsf(a) >= fabsf(b);
  const float big = sw ? a : b, sml = sw ? b : a, t = sml / big, d = 1.0f / fmaf(sml, t, big);
  const float cr = (sw ? fmaf(li, t, nr) : fmaf(nr, t, li)) * d, ci = (sw ? fmaf(-nr, t, li) : fmaf(li, t, -nr)) * d;
  asm volatile("st.shared.v4.f32 [%0], {%1,%2,%3,%4};" :: "r"(dst), "f"(lr), "f"(li), "f"(cr), "f"(ci) : "memory");
  __syncwarp();
}
DEVI void scan_load(Scan& s, uint32_t src) {
#pragma unroll
  for (int c = 0; c < 2; c++)
    asm volatile("ld.shared.v4.f32 {%0,%1,%2,%3}, [%4];" : "=f"(s.lr[c]), "=f"(s.li[c]), "=f"(s.cr[c]), "=f"(s.ci[c]) : "r"(src + 128 * c) : "memory");
}
DEVI uint64_t fresh(uint64_t d, uint32_t c) { return d + (c >> 24); }
DEVI uint32_t ld_epoch() { uint32_t l; asm volatile("mov.u32 %0, %%laneid;" : "=r"(l)); return ld_relaxed(&g_sync[SY_EPOCH + blockIdx.x + (l >> 5)]) + 1; }
DEVI uint32_t tid_x() { uint32_t v; asm volatile("mov.u32 %0, %%tid.x;" : "=r"(v)); return v; }
template <int T0, int T1> DEVI void scan_p1(Scan& s, const float (&ur)[32], const float (&ui)[32]) {
#pragma unroll
  for (int t = T0; t < T1; t++)
#pragma unroll
    for (int c = 0; c < 2; c++) {
      const int a = 4 * (t >> 1) + 2 * c + (t & 1);
      if (t == 0) { s.hr[c] = ur[a]; s.hi[c] = ui[a]; }
      else {
        const float tr = fmaf(s.lr[c], s.hr[c], ur[a]), ti = fmaf(s.lr[c], s.hi[c], ui[a]);
        const float nr = fmaf(-s.li[c], s.hi[c], tr); s.hi[c] = fmaf(s.li[c], s.hr[c], ti); s.hr[c] = nr;
      }
    }
}
DEVI void scan_pow16(Scan& s) {
  pin(s.lr); pin(s.li);
#pragma unroll
  for (int c = 0; c < 2; c++) { s.pr[c] = s.lr[c]; s.pi[c] = s.li[c]; csq(s.pr[c], s.pi[c]); csq(s.pr[c], s.pi[c]); csq(s.pr[c], s.pi[c]); csq(s.pr[c], s.pi[c]); }
}
DEVI void scan_quad(Scan& s, uint32_t* w, float4* dst, int q, uint32_t tag) {
#pragma unroll
  for (int c = 0; c < 2; c++) {
    float r = __shfl_up_sync(0xffffffffu, s.hr[c], 1, 4), i = __shfl_up_sync(0xffffffffu, s.hi[c], 1, 4);
    if (q < 1) { r = 0.f; i = 0.f; }
    s.hr[c] = fmaf(s.pr[c], r, fmaf(-s.pi[c], i, s.hr[c])); s.hi[c] = fmaf(s.pr[c], i, fmaf(s.pi[c], r, s.hi[c]));
    w[W_Q + 2 * c] = fu((q & 1) ? s.pr[c] : 1.f); w[W_Q + 2 * c + 1] = fu((q & 1) ? s.pi[c] : 0.f);
    csq(s.pr[c], s.pi[c]);
    r = __shfl_up_sync(0xffffffffu, s.hr[c], 2, 4); i = __shfl_up_sync(0xffffffffu, s.hi[c], 2, 4);
    if (q < 2) { r = 0.f; i = 0.f; }
    s.hr[c] = fmaf(s.pr[c], r, fmaf(-s.pi[c], i, s.hr[c])); s.hi[c] = fmaf(s.pr[c], i, fmaf(s.pi[c], r, s.hi[c]));
  }
  if (q == 3) asm volatile("st.relaxed.gpu.global.v4.b32 [%0], {%1,%2,%3,%4};" :: "l"(dst), "r"((fu(s.hr[0]) & ~1u) | tag), "r"(fu(s.hi[0])), "r"(fu(s.hr[1])), "r"(fu(s.hi[1])) : "memory");
}
DEVI void scan_excl(Scan& s, uint32_t* w, int q) {
#pragma unroll
  for (int c = 0; c < 2; c++) {
    const float r = __shfl_up_sync(0xffffffffu, s.hr[c], 1, 4), i = __shfl_up_sync(0xffffffffu, s.hi[c], 1, 4);
    s.hr[c] = q < 1 ? 0.f : r; s.hi[c] = q < 1 ? 0.f : i;
    float qr = uf(w[W_Q + 2 * c]), qi = uf(w[W_Q + 2 * c + 1]);
    if (q & 2) cmul(qr, qi, s.pr[c], s.pi[c]);
    w[W_Q + 2 * c] = fu(qr); w[W_Q + 2 * c + 1] = fu(qi);
    csq(s.pr[c], s.pi[c]);
  }
}
DEVI void scan_powf(Scan& s, uint32_t* w, int q) {
#pragma unroll
  for (int c = 0; c < 2; c++) {
    float r = s.pr[c], i = s.pi[c]; csq(r, i); csq(r, i); csq(r, i);
    float fr = (q & 1) ? 1.f : r, fi = (q & 1) ? 0.f : i;
    csq(r, i);
    if (!(q & 2)) cmul(fr, fi, r, i);
    w[W_F + 2 * c] = fu(fr); w[W_F + 2 * c + 1] = fu(fi);
  }
}
template <int H> DEVI void scan_reld(uint32_t* w, const float4* st, int p0, int q) {
  asm volatile("" : "+l"(st), "+r"(p0));
  st += (8 * q - 32) * 32;
#pragma unroll
  for (int k = 0; k < 4; k++) {
    uint32_t* v = w + W_L + 4 * k;
    asm volatile("{\n.reg .pred p;\nsetp.ge.s32 p, %5, %6;\n@p ld.relaxed.gpu.global.v4.u32 {%0,%1,%2,%3}, [%4];\n}"
                 : "+r"(v[0]), "+r"(v[1]), "+r"(v[2]), "+r"(v[3]) : "l"(st + (4 * H + k) * 32), "r"(p0), "r"(-4 * H - k) : "memory");
  }
}
template <int H> DEVI void scan_gld(uint32_t* w, const float4* st, int p0, int q, uint32_t tag) {
#pragma unroll
  for (int k = 0; k < 16; k++) w[W_L + k] = k & 3 ? 0 : tag;
  scan_reld<H>(w, st, p0, q);
}
template <int H> DEVI void scan_chk(uint32_t& c, uint32_t* w, const float4* st, int p0, int q, uint32_t tag) {
#pragma unroll 1
  while (__any_sync(0xffffffffu, ((w[W_L] ^ tag) | (w[W_L + 4] ^ tag) | (w[W_L + 8] ^ tag) | (w[W_L + 12] ^ tag)) & 1) && ++c < SPIN_MAX) scan_reld<H>(w, st, p0, q);
}
template <int H> DEVI void scan_horner(Scan& s, uint32_t* w) {
#pragma unroll
  for (int k = 0; k < 4; k++)
#pragma unroll
    for (int c = 0; c < 2; c++) {
      const float vr = uf(w[W_L + 4 * k + 2 * c]), vi = uf(w[W_L + 4 * k + 2 * c + 1]);
      const float gr = uf(w[W_G + 2 * c]), gi = uf(w[W_G + 2 * c + 1]);
      if (H == 0 && k == 0) { w[W_G + 2 * c] = fu(vr); w[W_G + 2 * c + 1] = fu(vi); }
      else { w[W_G + 2 * c] = fu(fmaf(s.pr[c], gr, fmaf(-s.pi[c], gi, vr))); w[W_G + 2 * c + 1] = fu(fmaf(s.pr[c], gi, fmaf(s.pi[c], gr, vi))); }
    }
}
DEVI void scan_carry(Scan& s, uint32_t* w) {
#pragma unroll
  for (int c = 0; c < 2; c++) {
    float gr = uf(w[W_G + 2 * c]), gi = uf(w[W_G + 2 * c + 1]);
    const float qr = uf(w[W_Q + 2 * c]), qi = uf(w[W_Q + 2 * c + 1]);
    cmul(gr, gi, uf(w[W_F + 2 * c]), uf(w[W_F + 2 * c + 1]));
    gr += __shfl_xor_sync(0xffffffffu, gr, 1); gi += __shfl_xor_sync(0xffffffffu, gi, 1);
    gr += __shfl_xor_sync(0xffffffffu, gr, 2); gi += __shfl_xor_sync(0xffffffffu, gi, 2);
    s.hr[c] = fmaf(qr, gr, fmaf(-qi, gi, s.hr[c])); s.hi[c] = fmaf(qr, gi, fmaf(qi, gr, s.hi[c]));
  }
}
template <int JJ> DEVI void scan_p2(Scan& s, uint32_t (&keep)[4], const float (&ur)[32], const float (&ui)[32], uint32_t* dst, bool odd) {
#pragma unroll
  for (int c = 0; c < 2; c++) {
    float o_r[2], o_i[2];
#pragma unroll
    for (int e = 0; e < 2; e++) {
      const int a = 4 * JJ + 2 * c + e;
      const float tr = fmaf(s.lr[c], s.hr[c], ur[a]), ti = fmaf(s.lr[c], s.hi[c], ui[a]);
      const float nr = fmaf(-s.li[c], s.hi[c], tr); s.hi[c] = fmaf(s.li[c], s.hr[c], ti); s.hr[c] = nr;
      o_r[e] = fmaf(s.cr[c], s.hr[c], -s.ci[c] * s.hi[c]); o_i[e] = fmaf(-s.cr[c], s.hi[c], -s.ci[c] * s.hr[c]);
    }
#pragma unroll
    for (int m = 0; m < 2; m++) {
      const uint32_t v = m ? pack2(o_i[0], o_i[1]) : pack2(o_r[0], o_r[1]);
      if constexpr ((JJ & 1) == 0) keep[2 * c + m] = v;
      else {
        const uint32_t k = keep[2 * c + m], rv = __shfl_xor_sync(0xffffffffu, odd ? k : v, 1);
        asm volatile("st.global.v2.b32 [%0], {%1,%2};" :: "l"(dst + (m * DM + c * 8) * (SEQ / 2) + 4 * (JJ - 1)), "r"(odd ? rv : k), "r"(odd ? v : rv) : "memory");
      }
    }
  }
}
DEVI void pin_s(Scan& s) { pin(s.hr); pin(s.hi); pin(s.pr); pin(s.pi); }
template <int A, int N> DEVI void pin_w(uint32_t* w) {
#pragma unroll
  for (int i = A; i < A + N; i++) asm volatile("" : "+r"(w[i]) :: "memory");
}

DEVI float silu2(float v) {
  float e, r;
  asm("ex2.approx.ftz.f32 %0, %1;" : "=f"(e) : "f"(v * -1.4426950408889634f));
  asm("rcp.approx.ftz.f32 %0, %1;" : "=f"(r) : "f"(fmaf(e, 0.5f, 0.5f)));
  return v * r;
}
template <int A0, int A1> DEVI void epi_silu(float (&z)[32], const uint32_t (&zr)[16], float (&t)[32], const float (&s0)[32]) {
#pragma unroll
  for (int a = A0; a < A1; a++) {
    z[a] = silu2(z[a] + ((a & 1) ? bhi(zr[a >> 1]) : blo(zr[a >> 1])));
    t[a] = fmaf(z[a], s0[a], t[a]);
    asm volatile("" : "+f"(z[a]), "+f"(t[a]) :: "memory");
  }
}
template <int JJ> DEVI void epi_x(float (&t)[32], float (&s0)[32], const uint32_t (&dh)[8], uint32_t xa, uint32_t xna) {
  uint32_t xv[4], nv[4];
  ldsm4(xv, xa ^ (JJ << 4)); ldsm4(nv, xna ^ (JJ << 4));
#pragma unroll
  for (int p = 0; p < 4; p++) {
    const uint32_t xd = hmul2(nv[p], dh[JJ + (p >> 1)]);
    const int a = 4 * JJ + 2 * p;
    t[a] = blo(xv[p]); t[a + 1] = bhi(xv[p]); s0[a] = blo(xd); s0[a + 1] = bhi(xd);
    asm volatile("" : "+f"(t[a]), "+f"(t[a + 1]), "+f"(s0[a]), "+f"(s0[a + 1]) :: "memory");
  }
}
DEVI void epi_store(float* o, const float (&t)[32], const float (&g2)[32], const float (&y)[32]) {
#pragma unroll
  for (int jj = 0; jj < 8; jj++)
#pragma unroll
    for (int r = 0; r < 2; r++) {
      const int a = 4 * jj + 2 * r;
      asm volatile("st.global.v2.f32 [%0], {%1,%2};" :: "l"(o + r * 2 * DM + 8 * jj), "f"(fmaf(g2[a], y[a], t[a])), "f"(fmaf(g2[a + 1], y[a + 1], t[a + 1])) : "memory");
    }
}
DEVI void ld_z(uint32_t (&zr)[16], const uint4* p) {
#pragma unroll
  for (int k = 0; k < 4; k++)
    asm volatile("ld.relaxed.gpu.global.v4.u32 {%0,%1,%2,%3}, [%4];" : "=r"(zr[4 * k]), "=r"(zr[4 * k + 1]), "=r"(zr[4 * k + 2]), "=r"(zr[4 * k + 3]) : "l"(p + k * 32) : "memory");
}
DEVI void ld_dh(uint32_t (&dh)[8], const __nv_bfloat16* d) {
#pragma unroll
  for (int k = 0; k < 8; k++) dh[k] = hmul2(__ldg((const uint32_t*)(d + 8 * k)), 0x3f003f00u);
}
DEVI int blk_of(int j, int b) { return b == 0 ? 8 : ((j + b) & 7); }

constexpr uint32_t UNIT = 24576;
struct Ring { uint32_t o, ph; };
DEVI void ring_next(Ring& r) { r.o += 8; if (r.o == 40) { r.o = 0; r.ph ^= 1; } }

DEVI void spare_consumer(const Params& P, uint32_t sb, int warp, int lane) {
  const uint32_t tag = ld_epoch() & 1;
  const int wg = warp >> 2, w = warp & 3, g = lane >> 2, q = lane & 3, sp = blockIdx.x - 128;
  const uint32_t bar = sb + OFF_BAR, rb = bar + 40 * wg;
  const uint64_t d0 = P.desc + ((sb & 0x3FFFF) >> 4), dr = d0 + 9 * 1024 + wg * 512;
  uint32_t c = 0, prev = 0;
  Ring rg = {0, 0};
  Scan s;
  scan_load(s, sb + OFF_PAR + (16 * w + g) * 16);
  if (wg) asm volatile("bar.sync 1, 256;" ::: "memory");
  mbar_wait(c, bar + 8 * B_RES, 0);
#pragma unroll 1
  for (int r = 0; r < 4; r++) {
    float ur[32], ui[32];
    uint32_t wk[32], keep[4];
#pragma unroll 1
    for (int u = 0; u < 9; u++) {
      mbar_wait(c, rb + 8 * B_FULL + rg.o, rg.ph);
      wg_fence();
      const uint64_t a = d0 + u * 1024, b = dr + rg.o * 128;
      wg_ss64p<0, 0, 0, 0>(ur, a, b, u); wg_ss64p<0, 0, 512, 0>(ui, a, b, u);
      sfor<1, 4>([&](auto K) { wg_ss64<0, 0, 2 * K.v, 2 * K.v>(ur, a, b); wg_ss64<0, 0, 512 + 2 * K.v, 2 * K.v>(ui, a, b); });
      wg_commit();
      wg_wait<1>();
      mbar_arrive_warp_if(rb + 8 * B_EMPTY + prev, u);
      prev = rg.o;
      ring_next(rg);
    }
    wg_wait<0>();
    mbar_arrive_warp(rb + 8 * B_EMPTY + prev);
    mbar_arrive_warp_if(bar + 8 * B_XN, r == 3);
    if (r + wg == 0) asm volatile("bar.arrive 1, 256;" ::: "memory");
    pin(ur); pin(ui);
    TRC(1 + 4 * r);
    const int seg = 8 * r + 4 * wg + sp;
    float4* stp = g_state + 8 * 1024 + seg * 32 + w * 8 + g;
    uint32_t* hsp = (uint32_t*)g_hsT + (size_t)(512 + 16 * w + g) * (SEQ / 2) + seg * 32 + (q & 1) * 4 + (q & 2);
    scan_pow16(s);
    scan_p1<0, 16>(s, ur, ui);
    scan_quad(s, wk, stp, q, tag);
    scan_gld<0>(wk, stp, seg - 32 + 8 * q, q, tag);
    scan_excl(s, wk, q); scan_powf(s, wk, q);
    TRC(2 + 4 * r);
    scan_chk<0>(c, wk, stp, seg - 32 + 8 * q, q, tag); scan_horner<0>(s, wk);
    scan_gld<1>(wk, stp, seg - 32 + 8 * q, q, tag); scan_chk<1>(c, wk, stp, seg - 32 + 8 * q, q, tag); scan_horner<1>(s, wk);
    TRC(3 + 4 * r);
    scan_carry(s, wk);
    sfor<0, 8>([&](auto J) { scan_p2<J.v>(s, keep, ur, ui, hsp, q & 1); });
    __syncwarp(); mbar_arrive_warp(bar + 8 * (B_HS + wg));
    TRC(4 + 4 * r);
  }
  mbar_wait(c, bar + 8 * B_G0, 0);
#pragma unroll 1
  for (int r = 0; r < 4; r++) {
    float y[32];
#pragma unroll 1
    for (int u = 0; u < 18; u++) {
      mbar_wait(c, rb + 8 * B_FULL + rg.o, rg.ph);
      wg_fence();
      const uint64_t a = dr + rg.o * 128, b = d0 + u * 512;
      wg_ss64p<1, 0, 0, 0>(y, a, b, u); wg_ss64<1, 0, 128, 2>(y, a, b); wg_ss64<1, 0, 256, 4>(y, a, b); wg_ss64<1, 0, 384, 6>(y, a, b);
      wg_commit();
      wg_wait<1>();
      mbar_arrive_warp_if(rb + 8 * B_EMPTY + prev, u);
      prev = rg.o;
      ring_next(rg);
    }
    wg_wait<0>();
    mbar_arrive_warp(rb + 8 * B_EMPTY + prev);
    pin(y);
    float4* yp = g_y8 + ((8 * r + 4 * wg + sp) * 4 + w) * 256 + lane;
#pragma unroll
    for (int k = 0; k < 8; k++) yp[k * 32] = make_float4(y[4 * k], y[4 * k + 1], y[4 * k + 2], y[4 * k + 3]);
    __syncwarp();
    mbar_arrive_warp(bar + 8 * (B_DR + wg));
    TRC(20 + r);
  }
  spin_check(c);
}

template <int T> DEVI void tile_end(uint32_t (&h)[144], float (&acc)[64]) {
  pin(acc);
#pragma unroll
  for (int r = 0; r < 16; r++) {
    h[16 * T + r] = pack2(acc[2 * r] * acc[32 + 2 * r], acc[2 * r + 1] * acc[33 + 2 * r]);
    asm volatile("" : "+r"(h[16 * T + r]) :: "memory");
  }
}

#define IDS const int tx = tid_x(), lane = tx & 31, warp = tx >> 5, w = warp & 3, g = lane >> 2, q = lane & 3; (void)w; (void)g; (void)q
DEVI void main_consumer(const Params& P, uint32_t sb, int wg) {
  const uint32_t bar = sb + OFF_BAR;
  const int j = blockIdx.x & 7, mi = blockIdx.x >> 3;
  uint64_t d0 = P.desc + ((sb & 0x3FFFF) >> 4), dx = d0 + wg * 512;
  uint32_t c = 0, h[144];
  Ring rg = {32, 1};
  uint32_t prev = 24;
  {
    float acc[64];
    Scan s;
    {
      IDS;
      {
        const uint4 zz = make_uint4(0, 0, 0, 0);
        uint4* zp = g_z + (mi * 9 + j) * 1024 + warp * 128 + lane;
#pragma unroll
        for (int k = 0; k < 4; k++) zp[k * 32] = zz;
        if (wg == 0) g_z[(mi * 9 + 8) * 1024 + j * 128 + w * 32 + lane] = zz;
      }
      constexpr int NKEEP = 8;
      uint32_t xv[144], one[8];
      float d[2][2][4];
#pragma unroll
      for (int k = 0; k < 16; k++) (&d[0][0][0])[k] = 0.f;
#pragma unroll
      for (int k = 0; k < 8; k++) one[k] = __shfl_sync(0xffffffffu, lane < 8 ? 0x3f803f80u : 0u, k);
      const uint32_t la = sb + (16 * warp + (lane & 7) + 8 * (lane >> 4)) * 128 + ((((lane >> 3) & 1) ^ (lane & 7)) << 4);
      const uint32_t sa = sb + (16 * warp + (lane & 15)) * 128 + (((lane >> 4) ^ (lane & 7)) << 4);
#pragma unroll
      for (int u = 0; u < 9; u++) {
        if ((u & 3) == 0) { mbar_wait(c, bar + 8 * (B_X0 + (u >> 2)) + wg * 24, 0); TRC(144 + (u >> 2)); }
#pragma unroll
        for (int k = 0; k < 4; k++) ldsm4(&xv[16 * u + 4 * k], (la ^ (k << 5)) + u * SLOT);
#pragma unroll
        for (int k = 0; k < 4; k++)
#pragma unroll
          for (int r = 0; r < 2; r++) {
            const uint32_t v0 = xv[16 * u + 4 * k + 2 * r], v1 = xv[16 * u + 4 * k + 2 * r + 1];
            mma16816(d[r][k & 1], v0, one[4 * r + 2 * (k & 1)], v1, one[4 * r + 2 * (k & 1) + 1], v0, v1);
          }
      }
      mbar_wait(c, bar + 8 * B_FULL, 0);
      TRC(140);
      const int src = 4 * g + (g >> 1);
      uint32_t rh2[2], rl2[2], c2[2];
#pragma unroll
      for (int r = 0; r < 2; r++) {
        float ss = (g & 1) ? d[r][0][1] + d[r][1][1] : d[r][0][0] + d[r][1][0];
        float sm = (g & 1) ? d[r][0][3] + d[r][1][3] : d[r][0][2] + d[r][1][2];
        ss = __shfl_sync(0xffffffffu, ss, src); sm = __shfl_sync(0xffffffffu, sm, src);
        const float mean = sm * (1.0f / DM);
        const float var = fmaxf(fmaf(-mean, mean, ss * (1.0f / DM)), 0.f);
        float sd, rs;
        asm("sqrt.approx.f32 %0, %1;" : "=f"(sd) : "f"(bhi(pack2(0.f, bhi(pack2(0.f, var)) + 1e-5f))));
        asm("rcp.approx.f32 %0, %1;" : "=f"(rs) : "f"(bhi(pack2(0.f, sd))));
        rh2[r] = pack2(rs, rs);
        const float rl = rs - bhi(rh2[r]), cc = -bhi(pack2(0.f, mean)) * rs;
        rl2[r] = pack2(rl, rl); c2[r] = pack2(cc, cc);
      }
      auto norm = [&](auto U) {
#pragma unroll
        for (int k = 0; k < 4; k++) {
          uint32_t* v = &xv[16 * U.v + 4 * k];
          const uint32_t t1 = U.v < NKEEP ? v[2] : v[1], t2 = U.v < NKEEP ? v[1] : v[2];
          v[0] = hfma2(v[0], rh2[0], hfma2(v[0], rl2[0], c2[0])); v[1] = hfma2(t1, rh2[1], hfma2(t1, rl2[1], c2[1]));
          v[2] = hfma2(t2, rh2[0], hfma2(t2, rl2[0], c2[0])); v[3] = hfma2(v[3], rh2[1], hfma2(v[3], rl2[1], c2[1]));
          stsm4((sa ^ (k << 5)) + U.v * SLOT, v);
        }
      };
      norm(IC<0>{});
      TRC(0);
      sfor<0, 9>([&](auto U) {
        constexpr uint32_t u = U.v, b = (9 + u % 5) * 1024;
        if constexpr (u == 5) d0 = fresh(d0, c);
        wg_fence();
        if constexpr (u == 0) wg_rs128z<1, b>(acc, &xv[16 * u], d0); else wg_rs128<1, b>(acc, &xv[16 * u], d0);
        wg_rs128<1, b + 128>(acc, &xv[16 * u + 4], d0);
        if constexpr (u + 1 >= NKEEP && u < 8) {
#pragma unroll
          for (int k = 0; k < 4; k++) ldsm4(&xv[16 * u + 16 + 4 * k], (sa ^ (k << 5)) + (u + 1) * SLOT);
        }
        if constexpr (u == 8) {
          fence_async_smem();
          if (wg == 0) asm volatile("bar.sync 1, 128;" ::: "memory"); else asm volatile("bar.sync 2, 128;" ::: "memory");
          mbar_arrive_warp(bar + 8 * B_XN);
        }
        mbar_wait_f(c, bar + 8 * (B_FULL + (u + 1) % 5), ((u + 1) / 5) & 1);
        if constexpr (u < 8) norm(IC<u + 1>{});
        if constexpr (u == 8) { scan_load(s, sb + OFF_PAR + ((tid_x() & 96) * 2 + (tid_x() & 28)) * 4); scan_pow16(s); pin(s.pr); pin(s.pi); }
        wg_rs128<1, b + 256>(acc, &xv[16 * u + 8], d0);
        wg_commit();
        if constexpr (u > 0) { wg_wait<1>(); mbar_arrive_warp(bar + 8 * (B_EMPTY + (u - 1) % 5)); }
        wg_rs128<1, b + 384>(acc, &xv[16 * u + 12], d0);
        wg_commit();
      });
    }
    TRC(9);
    float ur[32], ui[32];
#pragma unroll 1
    for (int u = 0; u < 9; u++) {
      wg_fence();
      const uint64_t a = d0 + 9 * 1024 + rg.o * 128, b = dx + u * 1024;
      wg_ss64p<0, 0, 0, 0>(ur, a, b, u); wg_ss64p<0, 0, 512, 0>(ui, a, b, u);
      wg_ss64<0, 0, 2, 2>(ur, a, b); wg_ss64<0, 0, 514, 2>(ui, a, b);
      wg_commit();
      wg_wait<1>();
      mbar_arrive_warp(bar + 8 * B_EMPTY + prev);
      prev = rg.o;
      ring_next(rg);
      wg_ss64<0, 0, 4, 4>(ur, a, b); wg_ss64<0, 0, 516, 4>(ui, a, b);
      mbar_wait_f(c, bar + 8 * B_FULL + rg.o, rg.ph);
      wg_ss64<0, 0, 6, 6>(ur, a, b); wg_ss64<0, 0, 518, 6>(ui, a, b);
      wg_commit();
    }
    tile_end<0>(h, acc);
    TRC(18);
    IDS;
    const uint32_t tag = ld_epoch() & 1;
    const int seg = mi * 2 + wg;
    float4* stp = g_state + j * 1024 + seg * 32 + w * 8 + g;
    uint32_t* hsp = (uint32_t*)g_hsT + (size_t)(j * 64 + 16 * w + g) * (SEQ / 2) + seg * 32 + (q & 1) * 4 + (q & 2);
    uint32_t wk[32], keep[4];
    sfor<1, 4>([&](auto T) {
      constexpr int t = T.v;
      sfor<0, 9>([&](auto U) {
        constexpr uint32_t u = U.v, S = 9 + 9 * t + u, sg = S - 18, a = u * 1024, b = (9 + S % 5) * 1024;
        if constexpr (u == 0) dx = fresh(dx, c);
        if constexpr (sg % 5 == 0) d0 = fresh(d0, c);
        if constexpr (u == 0) { wg_fence(); wg_ss128p<0, 1, a, b>(acc, dx, d0, (int)P.desc & 1); }
        else wg_ss128<0, 1, a, b>(acc, dx, d0);
        wg_ss128<0, 1, a + 2, b + 128>(acc, dx, d0);
        mbar_wait_f(c, bar + 8 * (B_FULL + (S + 1) % 5), ((S + 1) / 5) & 1);
        wg_ss128<0, 1, a + 4, b + 256>(acc, dx, d0);
        wg_commit();
        if constexpr (u > 0 || t == 1) { wg_wait<1>(); mbar_arrive_warp(bar + 8 * (B_EMPTY + (S - 1) % 5)); }
        wg_ss128<0, 1, a + 6, b + 384>(acc, dx, d0);
        wg_commit();
        if constexpr (sg == 0) { pin(ur); pin(ui); } else pin_s(s);
        if constexpr (sg < 4) scan_p1<4 * sg, 4 * sg + 4>(s, ur, ui);
        if constexpr (sg == 4) { scan_quad(s, wk, stp, q, tag); pin_w<W_Q, 4>(wk); }
        if constexpr (sg == 5) { scan_excl(s, wk, q); pin_w<W_Q, 4>(wk); }
        if constexpr (sg == 6) { scan_powf(s, wk, q); pin_w<W_F, 4>(wk); }
        if constexpr (sg == 9) scan_gld<0>(wk, stp, seg - 32 + 8 * q, q, tag);
        if constexpr (sg == 12) {
          scan_chk<0>(c, wk, stp, seg - 32 + 8 * q, q, tag); wg_fence();
          scan_horner<0>(s, wk); pin_w<W_G, 4>(wk); scan_gld<1>(wk, stp, seg - 32 + 8 * q, q, tag);
        }
        if constexpr (sg == 15) { scan_chk<1>(c, wk, stp, seg - 32 + 8 * q, q, tag); wg_fence(); scan_horner<1>(s, wk); pin_w<W_G, 4>(wk); }
        if constexpr (sg == 16) { pin_w<W_G, 4>(wk); scan_carry(s, wk); }
        if constexpr (sg >= 18 && sg < 26) { scan_p2<sg - 18>(s, keep, ur, ui, hsp, q & 1); if constexpr (!(sg & 1)) pinu(keep); }
        if constexpr (sg == 25) { __syncwarp(); mbar_arrive_warp(bar + 8 * (B_HS + wg)); }
        if constexpr (sg < 25) pin_s(s);
      });
      wg_wait<0>();
      mbar_arrive_warp(bar + 8 * (B_EMPTY + (17 + 9 * t) % 5));
      tile_end<t>(h, acc);
      TRC(18 + 9 * t);
    });
  }
  rg.o = 0; rg.ph = 1;
  sfor<4, 9>([&](auto T) {
    float acc[64];
#pragma unroll 1
    for (int u = 0; u < 9; u++) {
      wg_fence();
      const uint64_t a = dx + u * 1024, b = d0 + 9 * 1024 + rg.o * 128;
      wg_ss128p<0, 1, 0, 0>(acc, a, b, u); wg_ss128<0, 1, 2, 128>(acc, a, b);
      const uint32_t cur = rg.o;
      ring_next(rg);
      mbar_wait_f(c, bar + 8 * B_FULL + rg.o, rg.ph);
      wg_ss128<0, 1, 4, 256>(acc, a, b);
      wg_commit();
      wg_wait<1>();
      mbar_arrive_warp_if(bar + 8 * B_EMPTY + prev, u);
      prev = cur;
      wg_ss128<0, 1, 6, 384>(acc, a, b);
      wg_commit();
    }
    if constexpr (T.v == 8) mbar_wait(c, bar + 8 * B_FULLT, 0);
    wg_wait<0>();
    mbar_arrive_warp(bar + 8 * B_EMPTY + prev);
    tile_end<T.v>(h, acc);
    TRC(18 + 9 * T.v);
  });
  float y[32], z[32];
  {
    uint32_t o = 0, ph = 0;
    IDS;
    const uint32_t stg = sb + 13 * SLOT + warp * 2048 + lane * 16;
#pragma unroll 1
    for (int b = 0; b < 9; b++) {
      const uint64_t db = d0 + 1024 + o * (UNIT / 128);
      sfor<0, 3>([&](auto I) {
        constexpr int i = I.v;
        sfor<0, 12>([&](auto K) {
          constexpr uint32_t k = K.v, ob = i * (UNIT / 16) + k * 128;
          if constexpr (i == 0 && k == 0) { wg_fence(); wg_rs64z<1, ob>(z, &h[48 * i + 4 * k], db); } else wg_rs64<1, ob>(z, &h[48 * i + 4 * k], db);
          if constexpr (k == 4) {
            wg_commit();
            wg_wait<1>();
            if constexpr (i > 0) mbar_arrive_warp(bar + 8 * (B_EMPTYT + i - 1) + o);
            else mbar_arrive_warp_if(bar + 8 * (B_EMPTYT + 3) + (o ^ 32), b);
          }
          if constexpr (k == 6 && i == 2) mbar_wait_f(c, bar + 8 * (B_DF + wg), b & 1);
          if constexpr (k == 8) mbar_wait_f(c, bar + 8 * (B_FULLT + i + 1) + o, ph);
          if constexpr (k == 10 && i == 2) mbar_wait_f(c, bar + 8 * B_FULLT + (o ^ 32), ph ^ (o >> 5));
        });
        wg_commit();
      });
      constexpr uint32_t O = 3 * (UNIT / 16);
      const uint64_t da = db + wg * 512;
      wg_ss64p<1, 0, O, O + 1024>(y, da, db, b); wg_ss64<1, 0, O + 128, O + 1026>(y, da, db);
      wg_commit();
      wg_wait<1>();
      pin(z);
      sfor<0, 4>([&](auto K) {
        constexpr int k = K.v;
        asm volatile("{\n.reg .pred p;\nsetp.ne.b32 p, %5, 8;\n@p st.shared.v4.b32 [%0], {%1,%2,%3,%4};\n}" :: "r"(stg + k * 512), "r"(pack2(z[8 * k], z[8 * k + 1])),
                     "r"(pack2(z[8 * k + 2], z[8 * k + 3])), "r"(pack2(z[8 * k + 4], z[8 * k + 5])), "r"(pack2(z[8 * k + 6], z[8 * k + 7])), "r"(b) : "memory");
        if constexpr (k == 1) {
          wg_ss64<1, 0, O + 256, O + 1028>(y, da, db); wg_ss64<1, 0, O + 384, O + 1030>(y, da, db);
          wg_commit();
          mbar_arrive_warp(bar + 8 * (B_EMPTYT + 2) + o);
        }
      });
      __syncwarp();
      mbar_arrive_warp(bar + 8 * (B_DR + wg));
      TRC(91 + b);
      ph ^= o >> 5; o ^= 32;
    }
  }
  IDS;
  float tt[32], s0[32];
  uint32_t zr[16], dh[8];
  uint32_t e_x[2], e_n[2], e_z[2], e_d;
  float4 e_y;
  const uint32_t lsm = (wg * 64 + 16 * w + (lane & 15)) * 128 + (((lane >> 4) ^ (lane & 7)) << 4);
  const size_t orow = (size_t)(mi * 128 + wg * 64 + 16 * (g >> 1) + 4 * w + (g & 1)) * DM + 2 * q;
  sfor<0, 9>([&](auto TT) {
    constexpr int T = TT.v, U = (4 + T) & 7;
    constexpr uint32_t O = 1024 + U * (UNIT / 16);
    if constexpr (T == 0) wg_fence();
    wg_ss64<1, 0, O, O + 1024>(y, dx, d0); wg_ss64<1, 0, O + 128, O + 1026>(y, dx, d0);
    if constexpr (T < 8) mbar_wait_f(c, bar + 8 * (B_FULLT + ((U + 1) & 7)), ((37 + T) >> 3) & 1);
    wg_ss64<1, 0, O + 256, O + 1028>(y, dx, d0); wg_ss64<1, 0, O + 384, O + 1030>(y, dx, d0);
    wg_commit();
    if constexpr (T < 2) { wg_wait<1>(); mbar_arrive_warp(bar + 8 * (B_EMPTYT + U - 1)); }
    if constexpr (T == 0) {
      ld_dh(dh, P.dskip + j * 64 + 2 * q);
      e_d = __ldg((const uint32_t*)(P.dskip + 512 + 8 * j + 2 * q));
      e_x[0] = __ldg((const uint32_t*)(P.x + orow + 512 + 8 * j)); e_x[1] = __ldg((const uint32_t*)(P.x + orow + 512 + 8 * j + 2 * DM));
    }
    if constexpr (T == 2) {
      mbar_wait_f(c, bar + 8 * (B_Z + wg), 0);
      ld_z(zr, g_z + (mi * 9 + j) * 1024 + warp * 128 + lane);
      const uint32_t* np = (const uint32_t*)(g_xn + (mi * 9 + 8) * 1024 + (16 * warp + g) * 8 + (j ^ g)) + q;
      e_n[0] = ld_relaxed(np); e_n[1] = ld_relaxed(np + 256);
      const uint32_t* zp = (const uint32_t*)(g_z + (mi * 9 + 8) * 1024 + warp * 128 + (j >> 1) * 32 + lane) + 2 * (j & 1);
      asm volatile("ld.relaxed.gpu.global.v2.u32 {%0,%1}, [%2];" : "=r"(e_z[0]), "=r"(e_z[1]) : "l"(zp) : "memory");
      asm volatile("ld.relaxed.gpu.global.v4.f32 {%0,%1,%2,%3}, [%4];" : "=f"(e_y.x), "=f"(e_y.y), "=f"(e_y.z), "=f"(e_y.w)
                   : "l"(g_y8 + (mi * 8 + warp) * 256 + j * 32 + lane) : "memory");
    }
    if constexpr (T == 3) { pinu(dh); mbar_wait_f(c, bar + 8 * (B_XT + wg), 0); }
    if constexpr (T == 3 || T == 4) { epi_x<4 * T - 12>(tt, s0, dh, sb + 13 * SLOT + lsm, sb + lsm); epi_x<4 * T - 10>(tt, s0, dh, sb + 13 * SLOT + lsm, sb + lsm); }
    if constexpr (T == 5) pinu(zr);
    if constexpr (T >= 5) epi_silu<8 * T - 40, 8 * T - 32>(z, zr, tt, s0);
    if constexpr (T == 8) {
#pragma unroll
      for (int r = 0; r < 2; r++) {
        asm volatile("" : "+r"(e_z[r]) :: "memory");
        const uint32_t xd = hmul2(e_n[r], e_d);
        const float o0 = fmaf(silu2(blo(e_z[r])), fmaf(blo(xd), 0.5f, r ? e_y.z : e_y.x), blo(e_x[r]));
        const float o1 = fmaf(silu2(bhi(e_z[r])), fmaf(bhi(xd), 0.5f, r ? e_y.w : e_y.y), bhi(e_x[r]));
        asm volatile("st.global.v2.f32 [%0], {%1,%2};" :: "l"(P.out + orow + 512 + 8 * j + r * 2 * DM), "f"(o0), "f"(o1) : "memory");
      }
    }
    TRC(127 + T);
  });
  wg_wait<0>();
  pin(y);
  epi_store(P.out + orow + j * 64, tt, z, y);
  TRC(138);
  spin_check(c);
}

DEVI void load_x(const Params& P, uint32_t sb, int wg) {
  const uint32_t fb = sb + OFF_BAR + 8 * (B_X0 + 3 * wg), dst = sb + wg * 8192;
  const int seg = (blockIdx.x >> 3) * 2 + wg, c0 = (blockIdx.x & 7) * 64;
#pragma unroll
  for (int u = 0; u < 9; u++) {
    if ((u & 3) == 0) mbar_expect(fb + 8 * (u >> 2), u < 8 ? 4 * 8192 : 8192);
    tma_x(dst + u * SLOT, &P.xp, fb + 8 * (u >> 2), c0 + (c0 < DM - 64 * u ? 64 * u : 64 * u - DM), seg);
  }
}
DEVI void main_producer(const Params& P, uint32_t sb, int mi, int j) {
  const uint32_t bar = sb + OFF_BAR;
  uint32_t c = 0;
  Ring rg = {0, 1};
#pragma unroll 1
  for (int t = 0; t < 10; t++) {
    const CUtensorMap* m0 = t == 1 ? &P.bre : &P.wg;
    int kb = j;
#pragma unroll 1
    for (int u = 0; u < 9; u++) {
      const int c0 = t == 1 ? kb * 64 : j * DM + (t ? t - 1 : 0) * 64, c1 = t == 1 ? j * 64 : kb * 64;
      mbar_wait(c, bar + 8 * B_EMPTY + rg.o, rg.ph);
      if (elect()) {
        const uint32_t fb = bar + 8 * B_FULL + rg.o, dst = sb + 9 * SLOT + rg.o * 2048;
        mbar_expect(fb, SLOT); tma2d(dst, m0, fb, c0, c1); tma2d(dst + 8192, m0 + 1, fb, c0, c1);
      }
      TR(2, 9 * t + u);
      if (++kb == 9) kb = 0;
      ring_next(rg);
    }
  }
#pragma unroll 1
  for (int T = 0; T < 45; T++) {
    const int U = T & 7;
    if (T >= 8) mbar_wait(c, bar + 8 * (B_EMPTYT + U), ((T >> 3) - 1) & 1);
    else if (T >= 2 && T <= 4) mbar_wait(c, bar + 8 * B_EMPTY + (2 << T), 1);
    if (T == 3) mbar_wait(c, bar + 8 * B_G1, 0);
    const uint32_t fb = bar + 8 * (B_FULLT + U), dst = sb + SLOT + U * UNIT;
    if (elect()) {
      mbar_expect(fb, UNIT);
      if (T == 2) mbar_arrive(bar + 8 * B_FULL);
      if (T == 4) { mbar_arrive(bar + 8 * B_DF); mbar_arrive(bar + 8 * (B_DF + 1)); }
      if (T < 36 && (T & 3) != 3) {
        const int k0 = j * DM + (T & 3) * 192, c0 = blk_of(j, T >> 2) * 64;
        tma2d(dst, &P.wd, fb, c0, k0); tma2d(dst + 8192, &P.wd, fb, c0, k0 + 64); tma2d(dst + SLOT, &P.wd, fb, c0, k0 + 128);
      } else {
        const int k = T < 36 ? T >> 2 : T - 36;
        tma2d(dst, &P.hs, fb, mi * 128, (T < 36 ? k : 9 + k) * 64);
        tma2d(dst + 8192, &P.hs, fb, mi * 128 + 64, (T < 36 ? k : 9 + k) * 64);
        tma2d(dst + SLOT, T < 36 ? &P.cre : &P.cim, fb, k * 64, j * 64);
      }
    }
    TR(2, 100 + T);
  }
  spin_check(c);
}
DEVI void load_res(const CUtensorMap* m, uint32_t sb, uint32_t fb) {
  if (elect()) {
    mbar_expect(fb, 9 * SLOT);
#pragma unroll 1
    for (int u = 0; u < 18; u++) tma2d(sb + u * 8192, m + (u & 1), fb, (u >> 1) * 64, 512);
  }
}
DEVI void spare_producer(const Params& P, uint32_t sb, int sp, int wg, int lane, uint32_t ep) {
  const uint32_t bar = sb + OFF_BAR, rb = bar + 40 * wg, dst = sb + 9 * SLOT + wg * 8192;
  uint32_t c = 0;
  if (wg == 0) load_res(&P.bre, sb, bar + 8 * B_RES);
  Ring rg = {0, 1};
#pragma unroll 1
  for (int r = 0; r < 8; r++) {
    const int seg = 8 * (r & 3) + 4 * wg + sp;
    if (r == 4 && wg == 1) { mbar_wait(c, bar + 8 * B_XN, 0); mbar_wait(c, bar + 8 * B_XN, 1); load_res(&P.cre, sb, bar + 8 * B_G0); }
    const int ls = 8 * ((lane >> 1) & 3) + 4 * wg + sp;
    if (r == 0) poll_ge(&g_sync[SY_XN + (ls >> 1) * 32], ep * 8);
    if (r == 4 ? lane < 7 : r == 6) poll_ge(&g_sync[SY_HS + ls * 32 + (lane & 1)], lane & 1 ? ep : ep * 8);
    __syncwarp();
#pragma unroll 1
    for (int u = 0; u < (r < 4 ? 9 : 18); u++) {
      mbar_wait(c, rb + 8 * B_EMPTY + rg.o, rg.ph);
      if (elect()) {
        const uint32_t fb = rb + 8 * B_FULL + rg.o;
        mbar_expect(fb, 8192);
        if (r < 4) bulk_ld(dst + rg.o * 2048, g_xn + ((seg >> 1) * 9 + u) * 1024 + (seg & 1) * 512, 8192, fb);
        else tma2d(dst + rg.o * 2048, &P.hs, fb, seg * 64, (9 * (u & 1) + (u >> 1)) * 64);
      }
      ring_next(rg);
    }
  }
  spin_check(c);
}
DEVI void main_helper(const Params& P, uint32_t sb, int mi, int j, int lane, uint32_t ep) {
  const uint32_t bar = sb + OFF_BAR;
  uint32_t c = 0;
  if (lane < 8) asm volatile("prefetch.tensormap [%0];" :: "l"(&P.wg + lane) : "memory");
  mbar_wait(c, bar + 8 * (B_X0 + 1), 0);
#pragma unroll 1
  for (int gq = 0; gq < 3; gq++) {
    if (elect()) {
#pragma unroll 1
      for (int i = 0; i < 72; i++) pf_l2(P.pw[i & 1] + (size_t)(36 * mi + (i >> 1)) * FF + j * DM + gq * 192, 384);
    }
    if (gq == 0) {
      TR(2, 244);
      mbar_wait(c, bar + 8 * B_XN, 0);
      TR(2, 245);
      if (elect()) {
        bulk_st(g_xn + (mi * 9 + j) * 1024, sb, j == 7 ? 2 * SLOT : SLOT);
        asm volatile("cp.async.bulk.commit_group;\ncp.async.bulk.wait_group 0;" ::: "memory");
        TR(2, 246);
        red_inc(&g_sync[SY_XN + mi * 32]);
      }
    }
    asm volatile("nanosleep.u32 3000;");
  }
  if (elect()) {
#pragma unroll 1
    for (int i = 0; i < 9; i++) { pf_l2(P.pw[2] + (size_t)(j * DM + 36 * mi + 4 * i) * DM, 4 * DM * 2); asm volatile("nanosleep.u32 300;"); }
    pf_l2(P.pw[5] + (j * 64 + mi * 4) * DM, 4 * DM * 2); pf_l2(P.pw[6] + (j * 64 + mi * 4) * DM, 4 * DM * 2);
  }
  __syncwarp();
  TR(2, 248);
  if (lane < 4) poll_ge(&g_sync[SY_HS + (2 * mi + (lane >> 1)) * 32 + (lane & 1)], lane & 1 ? ep : ep * 8);
  __syncwarp();
  TR(2, 249);
  if (lane == 0) mbar_arrive(bar + 8 * B_G1);
  spin_check(c);
}
DEVI void wg_helper(const Params& P, uint32_t sb, int wg, int lane, uint32_t ep) {
  const uint32_t bar = sb + OFF_BAR + 8 * wg;
  const bool mainc = blockIdx.x < 128;
  const int j = mainc ? blockIdx.x & 7 : 8, mi = blockIdx.x >> 3, seg0 = mainc ? 2 * mi + wg : blockIdx.x - 128 + 4 * wg, nr = mainc ? 1 : 4;
  uint32_t c = 0;
#pragma unroll 1
  for (int r = 0; r < nr; r++) {
    const int seg = seg0 + 8 * r;
    mbar_wait(c, bar + 8 * B_HS, r & 1);
    TR(2, 223 + 12 * wg);
    if (lane == 0) { fence_async_all(); fence_gpu(); red_inc(&g_sync[SY_HS + seg * 32 + !mainc]); }
    __syncwarp();
    TR(2, 224 + 12 * wg);
  }
  if (mainc) {
    mbar_wait(c, sb + OFF_BAR + 8 * B_G1, 0);
    const uint32_t stg = sb + 13 * SLOT + wg * 8192;
#pragma unroll 1
    for (int b = 0; b < 8; b++) {
      mbar_wait(c, bar + 8 * B_DR, b & 1);
      TR(2, 225 + 12 * wg);
      if (elect()) {
        fence_async_smem();
        bulk_red(g_z + (mi * 9 + blk_of(j, b)) * 1024 + wg * 512, stg, 8192);
        asm volatile("cp.async.bulk.commit_group;\ncp.async.bulk.wait_group.read 0;" ::: "memory");
        mbar_arrive(bar + 8 * B_DF);
        TR(2, 226 + 12 * wg);
        if (b == 7) {
          mbar_expect(bar + 8 * B_XT, 8192); tma_x(stg, &P.xp, bar + 8 * B_XT, j * 64, seg0);
          asm volatile("cp.async.bulk.wait_group 0;" ::: "memory");
          TR(2, 227 + 12 * wg);
          red_inc(&g_sync[SY_Z + seg0 * 32]);
          poll_ge(&g_sync[SY_Z + seg0 * 32], ep * 9);
          TR(2, 229 + 12 * wg);
          mbar_arrive(bar + 8 * B_Z);
        }
      }
      __syncwarp();
    }
  } else {
#pragma unroll 1
    for (int r = 0; r < 4; r++) {
      mbar_wait(c, bar + 8 * B_DR, r & 1);
      if (lane == 0) { fence_gpu(); red_inc(&g_sync[SY_Z + (seg0 + 8 * r) * 32]); }
      __syncwarp();
    }
  }
  if (wg == 1 && lane == 0) st_relaxed(&g_sync[SY_EPOCH + blockIdx.x], ep);
  spin_check(c);
}

__global__ void __launch_bounds__(384, 1) fused_kernel(const __grid_constant__ Params P) {
  extern __shared__ __align__(1024) uint8_t smem_raw[];
  uint32_t sb = smem_u32(smem_raw);
  asm volatile("" : "+r"(sb));
  const int warp = __shfl_sync(0xffffffffu, threadIdx.x >> 5, 0), lane = threadIdx.x & 31;
  const int bid = blockIdx.x;
  TRC(255);
  const int ch = (bid < 128 ? bid & 7 : 8) * 64 + 16 * (warp & 3) + (lane >> 2) + 8 * (lane & 1);
  const __nv_bfloat16 p_re = P.lre[ch], p_im = P.lim[ch], p_dt = P.ldt[ch];
  if (warp <= 8 && elect()) {
    const uint32_t cnt = (warp & 4) ? (warp == 7 || bid >= 128 ? 4 : 8) : 1;
#pragma unroll
    for (int k = 0; k < 6; k++) mbar_init(sb + OFF_BAR + 48 * warp + 8 * k, cnt);
    asm volatile("fence.mbarrier_init.release.cluster;" ::: "memory");
    if (warp == 8 && bid < 128) load_x(P, sb, 0);
  }
  TR(2, 200 + warp);
  __syncthreads();
  if (warp >= 8) {
    asm volatile("setmaxnreg.dec.sync.aligned.u32 24;");
    if (warp >= 10) wg_helper(P, sb, warp - 10, lane, ld_epoch());
    else if (bid >= 128) spare_producer(P, sb, bid - 128, warp - 8, lane, ld_epoch());
    else if (warp == 9) main_helper(P, sb, bid >> 3, bid & 7, lane, ld_epoch());
    else {
      if (elect()) load_x(P, sb, 1);
      __syncwarp();
      main_producer(P, sb, bid >> 3, bid & 7);
    }
  } else {
    TRC(141);
    asm volatile("setmaxnreg.inc.sync.aligned.u32 240;");
    TRC(142);
    scan_params(sb + OFF_PAR + (ch & 63) * 16, __bfloat162float(p_re), __bfloat162float(p_im), __bfloat162float(p_dt));
    TRC(143);
    if (bid < 128) main_consumer(P, sb, warp >> 2); else spare_consumer(P, sb, warp, lane);
  }
}
typedef CUresult (*EncodeFn)(CUtensorMap*, CUtensorMapDataType, cuuint32_t, void*, const cuuint64_t*, const cuuint64_t*, const cuuint32_t*,
                             const cuuint32_t*, CUtensorMapInterleave, CUtensorMapSwizzle, CUtensorMapL2promotion, CUtensorMapFloatOOBfill);
static void make_map(EncodeFn enc, CUtensorMap* m, const void* ptr, int rank, const cuuint64_t* dims, const cuuint64_t* strides, const cuuint32_t* box) {
  const cuuint32_t es[5] = {1, 1, 1, 1, 1};
  enc(m, CU_TENSOR_MAP_DATA_TYPE_BFLOAT16, rank, (void*)ptr, dims, strides, box, es, CU_TENSOR_MAP_INTERLEAVE_NONE,
      CU_TENSOR_MAP_SWIZZLE_128B, CU_TENSOR_MAP_L2_PROMOTION_L2_128B, CU_TENSOR_MAP_FLOAT_OOB_FILL_NONE);
}
static void map2d(EncodeFn enc, CUtensorMap* m, const void* ptr, uint64_t inner, uint64_t outer) {
  const cuuint64_t dims[2] = {inner, outer}, strides[1] = {inner * 2};
  const cuuint32_t box[2] = {64, 64};
  make_map(enc, m, ptr, 2, dims, strides, box);
}

extern "C" void kernel_launch(void* const* d_in, const int* in_sizes, int n_in, void* d_out, int out_size) {
  void* fn = nullptr;
  cudaDriverEntryPointQueryResult st;
  cudaGetDriverEntryPoint("cuTensorMapEncodeTiled", &fn, cudaEnableDefault, &st);
  EncodeFn enc = (EncodeFn)fn;
  void* hs = nullptr;
  cudaGetSymbolAddress(&hs, g_hsT);
  Params P;
  map2d(enc, &P.wg, d_in[10], FF, DM); map2d(enc, &P.wu, d_in[11], FF, DM); map2d(enc, &P.wd, d_in[12], DM, FF);
  map2d(enc, &P.bre, d_in[3], DM, DM); map2d(enc, &P.bim, d_in[4], DM, DM);
  map2d(enc, &P.cre, d_in[5], DM, DM); map2d(enc, &P.cim, d_in[6], DM, DM);
  map2d(enc, &P.hs, hs, SEQ, 2 * DM);
  {
    const cuuint64_t dims[5] = {DM, 2, 4, 8, 32}, strides[4] = {DM * 2, 16 * DM * 2, 2 * DM * 2, 64 * DM * 2};
    const cuuint32_t box[5] = {64, 2, 4, 8, 1};
    make_map(enc, &P.xp, d_in[0], 5, dims, strides, box);
  }
  P.x = (const __nv_bfloat16*)d_in[0]; P.lre = (const __nv_bfloat16*)d_in[1]; P.lim = (const __nv_bfloat16*)d_in[2];
  P.ldt = (const __nv_bfloat16*)d_in[7]; P.dskip = (const __nv_bfloat16*)d_in[8];
  const int pi[7] = {10, 11, 12, 3, 4, 5, 6};
  for (int i = 0; i < 7; i++) P.pw[i] = (const __nv_bfloat16*)d_in[pi[i]];
  P.out = (float*)d_out;
  P.desc = DESC0;
  cudaFuncSetAttribute(fused_kernel, cudaFuncAttributeMaxDynamicSharedMemorySize, SMEM_BYTES);
  fused_kernel<<<132, 384, SMEM_BYTES, cudaStreamPerThread>>>(P);
}
```

```cpp
#include <cuda_runtime.h>
#include <cuda.h>
#include <cuda_bf16.h>
#include <stdint.h>

#define DEVI __device__ __forceinline__
template<int TA,int TB,uint32_t OA,uint32_t OB> DEVI void wg_ss64(float (&d)[32], uint64_t da, uint64_t db) {
  asm volatile("{\n.reg .pred p;\n.reg .b64 x,y;\nsetp.eq.b32 p,1,1;\nadd.s64 x,%32,%36;\nadd.s64 y,%33,%37;\n"
    "wgmma.mma_async.sync.aligned.m64n64k16.f32.bf16.bf16 "
    "{%0,%1,%2,%3,%4,%5,%6,%7,%8,%9,%10,%11,%12,%13,%14,%15,%16,%17,%18,%19,%20,%21,%22,%23,%24,%25,%26,%27,%28,%29,%30,%31},x,y,p,1,1,%34,%35;\n}\n"
    : "+f"(d[0]),"+f"(d[1]),"+f"(d[2]),"+f"(d[3]),"+f"(d[4]),"+f"(d[5]),"+f"(d[6]),"+f"(d[7]),"+f"(d[8]),"+f"(d[9]),"+f"(d[10]),"+f"(d[11]),"+f"(d[12]),"+f"(d[13]),"+f"(d[14]),"+f"(d[15]),"+f"(d[16]),"+f"(d[17]),"+f"(d[18]),"+f"(d[19]),"+f"(d[20]),"+f"(d[21]),"+f"(d[22]),"+f"(d[23]),"+f"(d[24]),"+f"(d[25]),"+f"(d[26]),"+f"(d[27]),"+f"(d[28]),"+f"(d[29]),"+f"(d[30]),"+f"(d[31])
    : "l"(da),"l"(db),"n"(TA),"n"(TB),"n"(OA),"n"(OB));
}
template<int TA,int TB,uint32_t OA,uint32_t OB> DEVI void wg_ss64p(float (&d)[32], uint64_t da, uint64_t db, int f) {
  asm volatile("{\n.reg .pred p;\n.reg .b64 x,y;\nsetp.ne.b32 p,%38,0;\nadd.s64 x,%32,%36;\nadd.s64 y,%33,%37;\n"
    "wgmma.mma_async.sync.aligned.m64n64k16.f32.bf16.bf16 "
    "{%0,%1,%2,%3,%4,%5,%6,%7,%8,%9,%10,%11,%12,%13,%14,%15,%16,%17,%18,%19,%20,%21,%22,%23,%24,%25,%26,%27,%28,%29,%30,%31},x,y,p,1,1,%34,%35;\n}\n"
    : "+f"(d[0]),"+f"(d[1]),"+f"(d[2]),"+f"(d[3]),"+f"(d[4]),"+f"(d[5]),"+f"(d[6]),"+f"(d[7]),"+f"(d[8]),"+f"(d[9]),"+f"(d[10]),"+f"(d[11]),"+f"(d[12]),"+f"(d[13]),"+f"(d[14]),"+f"(d[15]),"+f"(d[16]),"+f"(d[17]),"+f"(d[18]),"+f"(d[19]),"+f"(d[20]),"+f"(d[21]),"+f"(d[22]),"+f"(d[23]),"+f"(d[24]),"+f"(d[25]),"+f"(d[26]),"+f"(d[27]),"+f"(d[28]),"+f"(d[29]),"+f"(d[30]),"+f"(d[31])
    : "l"(da),"l"(db),"n"(TA),"n"(TB),"n"(OA),"n"(OB),"r"(f));
}
template<int TA,int TB,uint32_t OA,uint32_t OB> DEVI void wg_ss128(float (&d)[64], uint64_t da, uint64_t db) {
  asm volatile("{\n.reg .pred p;\n.reg .b64 x,y;\nsetp.eq.b32 p,1,1;\nadd.s64 x,%64,%68;\nadd.s64 y,%65,%69;\n"
    "wgmma.mma_async.sync.aligned.m64n128k16.f32.bf16.bf16 "
    "{%0,%1,%2,%3,%4,%5,%6,%7,%8,%9,%10,%11,%12,%13,%14,%15,%16,%17,%18,%19,%20,%21,%22,%23,%24,%25,%26,%27,%28,%29,%30,%31,%32,%33,%34,%35,%36,%37,%38,%39,%40,%41,%42,%43,%44,%45,%46,%47,%48,%49,%50,%51,%52,%53,%54,%55,%56,%57,%58,%59,%60,%61,%62,%63},x,y,p,1,1,%66,%67;\n}\n"
    : "+f"(d[0]),"+f"(d[1]),"+f"(d[2]),"+f"(d[3]),"+f"(d[4]),"+f"(d[5]),"+f"(d[6]),"+f"(d[7]),"+f"(d[8]),"+f"(d[9]),"+f"(d[10]),"+f"(d[11]),"+f"(d[12]),"+f"(d[13]),"+f"(d[14]),"+f"(d[15]),"+f"(d[16]),"+f"(d[17]),"+f"(d[18]),"+f"(d[19]),"+f"(d[20]),"+f"(d[21]),"+f"(d[22]),"+f"(d[23]),"+f"(d[24]),"+f"(d[25]),"+f"(d[26]),"+f"(d[27]),"+f"(d[28]),"+f"(d[29]),"+f"(d[30]),"+f"(d[31]),"+f"(d[32]),"+f"(d[33]),"+f"(d[34]),"+f"(d[35]),"+f"(d[36]),"+f"(d[37]),"+f"(d[38]),"+f"(d[39]),"+f"(d[40]),"+f"(d[41]),"+f"(d[42]),"+f"(d[43]),"+f"(d[44]),"+f"(d[45]),"+f"(d[46]),"+f"(d[47]),"+f"(d[48]),"+f"(d[49]),"+f"(d[50]),"+f"(d[51]),"+f"(d[52]),"+f"(d[53]),"+f"(d[54]),"+f"(d[55]),"+f"(d[56]),"+f"(d[57]),"+f"(d[58]),"+f"(d[59]),"+f"(d[60]),"+f"(d[61]),"+f"(d[62]),"+f"(d[63])
    : "l"(da),"l"(db),"n"(TA),"n"(TB),"n"(OA),"n"(OB));
}
template<int TA,int TB,uint32_t OA,uint32_t OB> DEVI void wg_ss128p(float (&d)[64], uint64_t da, uint64_t db, int f) {
  asm volatile("{\n.reg .pred p;\n.reg .b64 x,y;\nsetp.ne.b32 p,%70,0;\nadd.s64 x,%64,%68;\nadd.s64 y,%65,%69;\n"
    "wgmma.mma_async.sync.aligned.m64n128k16.f32.bf16.bf16 "
    "{%0,%1,%2,%3,%4,%5,%6,%7,%8,%9,%10,%11,%12,%13,%14,%15,%16,%17,%18,%19,%20,%21,%22,%23,%24,%25,%26,%27,%28,%29,%30,%31,%32,%33,%34,%35,%36,%37,%38,%39,%40,%41,%42,%43,%44,%45,%46,%47,%48,%49,%50,%51,%52,%53,%54,%55,%56,%57,%58,%59,%60,%61,%62,%63},x,y,p,1,1,%66,%67;\n}\n"
    : "+f"(d[0]),"+f"(d[1]),"+f"(d[2]),"+f"(d[3]),"+f"(d[4]),"+f"(d[5]),"+f"(d[6]),"+f"(d[7]),"+f"(d[8]),"+f"(d[9]),"+f"(d[10]),"+f"(d[11]),"+f"(d[12]),"+f"(d[13]),"+f"(d[14]),"+f"(d[15]),"+f"(d[16]),"+f"(d[17]),"+f"(d[18]),"+f"(d[19]),"+f"(d[20]),"+f"(d[21]),"+f"(d[22]),"+f"(d[23]),"+f"(d[24]),"+f"(d[25]),"+f"(d[26]),"+f"(d[27]),"+f"(d[28]),"+f"(d[29]),"+f"(d[30]),"+f"(d[31]),"+f"(d[32]),"+f"(d[33]),"+f"(d[34]),"+f"(d[35]),"+f"(d[36]),"+f"(d[37]),"+f"(d[38]),"+f"(d[39]),"+f"(d[40]),"+f"(d[41]),"+f"(d[42]),"+f"(d[43]),"+f"(d[44]),"+f"(d[45]),"+f"(d[46]),"+f"(d[47]),"+f"(d[48]),"+f"(d[49]),"+f"(d[50]),"+f"(d[51]),"+f"(d[52]),"+f"(d[53]),"+f"(d[54]),"+f"(d[55]),"+f"(d[56]),"+f"(d[57]),"+f"(d[58]),"+f"(d[59]),"+f"(d[60]),"+f"(d[61]),"+f"(d[62]),"+f"(d[63])
    : "l"(da),"l"(db),"n"(TA),"n"(TB),"n"(OA),"n"(OB),"r"(f));
}
template<int TB,uint32_t OB> DEVI void wg_rs64(float (&d)[32], const uint32_t* a, uint64_t db) {
  asm volatile("{\n.reg .pred p;\n.reg .b64 y;\nsetp.eq.b32 p,1,1;\nadd.s64 y,%36,%38;\n"
    "wgmma.mma_async.sync.aligned.m64n64k16.f32.bf16.bf16 "
    "{%0,%1,%2,%3,%4,%5,%6,%7,%8,%9,%10,%11,%12,%13,%14,%15,%16,%17,%18,%19,%20,%21,%22,%23,%24,%25,%26,%27,%28,%29,%30,%31},{%32,%33,%34,%35},y,p,1,1,%37;\n}\n"
    : "+f"(d[0]),"+f"(d[1]),"+f"(d[2]),"+f"(d[3]),"+f"(d[4]),"+f"(d[5]),"+f"(d[6]),"+f"(d[7]),"+f"(d[8]),"+f"(d[9]),"+f"(d[10]),"+f"(d[11]),"+f"(d[12]),"+f"(d[13]),"+f"(d[14]),"+f"(d[15]),"+f"(d[16]),"+f"(d[17]),"+f"(d[18]),"+f"(d[19]),"+f"(d[20]),"+f"(d[21]),"+f"(d[22]),"+f"(d[23]),"+f"(d[24]),"+f"(d[25]),"+f"(d[26]),"+f"(d[27]),"+f"(d[28]),"+f"(d[29]),"+f"(d[30]),"+f"(d[31])
    : "r"(a[0]),"r"(a[1]),"r"(a[2]),"r"(a[3]),"l"(db),"n"(TB),"n"(OB));
}
template<int TB,uint32_t OB> DEVI void wg_rs64z(float (&d)[32], const uint32_t* a, uint64_t db) {
  asm volatile("{\n.reg .pred p;\n.reg .b64 y;\nsetp.ne.b32 p,1,1;\nadd.s64 y,%36,%38;\n"
    "wgmma.mma_async.sync.aligned.m64n64k16.f32.bf16.bf16 "
    "{%0,%1,%2,%3,%4,%5,%6,%7,%8,%9,%10,%11,%12,%13,%14,%15,%16,%17,%18,%19,%20,%21,%22,%23,%24,%25,%26,%27,%28,%29,%30,%31},{%32,%33,%34,%35},y,p,1,1,%37;\n}\n"
    : "=f"(d[0]),"=f"(d[1]),"=f"(d[2]),"=f"(d[3]),"=f"(d[4]),"=f"(d[5]),"=f"(d[6]),"=f"(d[7]),"=f"(d[8]),"=f"(d[9]),"=f"(d[10]),"=f"(d[11]),"=f"(d[12]),"=f"(d[13]),"=f"(d[14]),"=f"(d[15]),"=f"(d[16]),"=f"(d[17]),"=f"(d[18]),"=f"(d[19]),"=f"(d[20]),"=f"(d[21]),"=f"(d[22]),"=f"(d[23]),"=f"(d[24]),"=f"(d[25]),"=f"(d[26]),"=f"(d[27]),"=f"(d[28]),"=f"(d[29]),"=f"(d[30]),"=f"(d[31])
    : "r"(a[0]),"r"(a[1]),"r"(a[2]),"r"(a[3]),"l"(db),"n"(TB),"n"(OB));
}
template<int TB,uint32_t OB> DEVI void wg_rs128(float (&d)[64], const uint32_t* a, uint64_t db) {
  asm volatile("{\n.reg .pred p;\n.reg .b64 y;\nsetp.eq.b32 p,1,1;\nadd.s64 y,%68,%70;\n"
    "wgmma.mma_async.sync.aligned.m64n128k16.f32.bf16.bf16 "
    "{%0,%1,%2,%3,%4,%5,%6,%7,%8,%9,%10,%11,%12,%13,%14,%15,%16,%17,%18,%19,%20,%21,%22,%23,%24,%25,%26,%27,%28,%29,%30,%31,%32,%33,%34,%35,%36,%37,%38,%39,%40,%41,%42,%43,%44,%45,%46,%47,%48,%49,%50,%51,%52,%53,%54,%55,%56,%57,%58,%59,%60,%61,%62,%63},{%64,%65,%66,%67},y,p,1,1,%69;\n}\n"
    : "+f"(d[0]),"+f"(d[1]),"+f"(d[2]),"+f"(d[3]),"+f"(d[4]),"+f"(d[5]),"+f"(d[6]),"+f"(d[7]),"+f"(d[8]),"+f"(d[9]),"+f"(d[10]),"+f"(d[11]),"+f"(d[12]),"+f"(d[13]),"+f"(d[14]),"+f"(d[15]),"+f"(d[16]),"+f"(d[17]),"+f"(d[18]),"+f"(d[19]),"+f"(d[20]),"+f"(d[21]),"+f"(d[22]),"+f"(d[23]),"+f"(d[24]),"+f"(d[25]),"+f"(d[26]),"+f"(d[27]),"+f"(d[28]),"+f"(d[29]),"+f"(d[30]),"+f"(d[31]),"+f"(d[32]),"+f"(d[33]),"+f"(d[34]),"+f"(d[35]),"+f"(d[36]),"+f"(d[37]),"+f"(d[38]),"+f"(d[39]),"+f"(d[40]),"+f"(d[41]),"+f"(d[42]),"+f"(d[43]),"+f"(d[44]),"+f"(d[45]),"+f"(d[46]),"+f"(d[47]),"+f"(d[48]),"+f"(d[49]),"+f"(d[50]),"+f"(d[51]),"+f"(d[52]),"+f"(d[53]),"+f"(d[54]),"+f"(d[55]),"+f"(d[56]),"+f"(d[57]),"+f"(d[58]),"+f"(d[59]),"+f"(d[60]),"+f"(d[61]),"+f"(d[62]),"+f"(d[63])
    : "r"(a[0]),"r"(a[1]),"r"(a[2]),"r"(a[3]),"l"(db),"n"(TB),"n"(OB));
}
template<int TB,uint32_t OB> DEVI void wg_rs128z(float (&d)[64], const uint32_t* a, uint64_t db) {
  asm volatile("{\n.reg .pred p;\n.reg .b64 y;\nsetp.ne.b32 p,1,1;\nadd.s64 y,%68,%70;\n"
    "wgmma.mma_async.sync.aligned.m64n128k16.f32.bf16.bf16 "
    "{%0,%1,%2,%3,%4,%5,%6,%7,%8,%9,%10,%11,%12,%13,%14,%15,%16,%17,%18,%19,%20,%21,%22,%23,%24,%25,%26,%27,%28,%29,%30,%31,%32,%33,%34,%35,%36,%37,%38,%39,%40,%41,%42,%43,%44,%45,%46,%47,%48,%49,%50,%51,%52,%53,%54,%55,%56,%57,%58,%59,%60,%61,%62,%63},{%64,%65,%66,%67},y,p,1,1,%69;\n}\n"
    : "=f"(d[0]),"=f"(d[1]),"=f"(d[2]),"=f"(d[3]),"=f"(d[4]),"=f"(d[5]),"=f"(d[6]),"=f"(d[7]),"=f"(d[8]),"=f"(d[9]),"=f"(d[10]),"=f"(d[11]),"=f"(d[12]),"=f"(d[13]),"=f"(d[14]),"=f"(d[15]),"=f"(d[16]),"=f"(d[17]),"=f"(d[18]),"=f"(d[19]),"=f"(d[20]),"=f"(d[21]),"=f"(d[22]),"=f"(d[23]),"=f"(d[24]),"=f"(d[25]),"=f"(d[26]),"=f"(d[27]),"=f"(d[28]),"=f"(d[29]),"=f"(d[30]),"=f"(d[31]),"=f"(d[32]),"=f"(d[33]),"=f"(d[34]),"=f"(d[35]),"=f"(d[36]),"=f"(d[37]),"=f"(d[38]),"=f"(d[39]),"=f"(d[40]),"=f"(d[41]),"=f"(d[42]),"=f"(d[43]),"=f"(d[44]),"=f"(d[45]),"=f"(d[46]),"=f"(d[47]),"=f"(d[48]),"=f"(d[49]),"=f"(d[50]),"=f"(d[51]),"=f"(d[52]),"=f"(d[53]),"=f"(d[54]),"=f"(d[55]),"=f"(d[56]),"=f"(d[57]),"=f"(d[58]),"=f"(d[59]),"=f"(d[60]),"=f"(d[61]),"=f"(d[62]),"=f"(d[63])
    : "r"(a[0]),"r"(a[1]),"r"(a[2]),"r"(a[3]),"l"(db),"n"(TB),"n"(OB));
}

constexpr int SEQ = 2048, DM = 576, FF = 4608;
constexpr uint32_t SLOT = 16384;
constexpr uint32_t OFF_BAR = 14 * SLOT;
constexpr uint32_t OFF_PAR = OFF_BAR + 512;
constexpr uint32_t OFF_D = OFF_PAR + 1024;
constexpr uint32_t SMEM_BYTES = OFF_D + 256;
constexpr int B_X0 = 48, B_P2 = 0, B_FULL = 2, B_FULLT = 7, B_XT = 15, B_DF = 17, B_Z = 19, B_RES = 21, B_G1 = 23,
              B_EMPTY = 24, B_EMPTYT = 29, B_XN = 37, B_HS = 44, B_DR = 46;
DEVI int vpair(int b) {
  const int k = b >> 1, t = k - 4, d = ((k - 36) * 37) >> 8;
  return k < 4 ? k : k < 36 ? (t & 7) * 8 + (t >> 3) + (t & 7 ? 0 : 4) : (k - 35 - 7 * d) * 8 + 4 + d;
}
#define CJ(b) ((int)(b) >= 128 ? 8 : vpair(b) & 7)
#define CM(b) ((vpair(b) >> 3) * 2 + ((int)(b) & 1))
constexpr uint32_t SPIN_MAX = 400000;

struct alignas(64) Params {
  CUtensorMap wg, wu, wd, bre, bim, cre, cim, hs2, hs, xp;
  const __nv_bfloat16 *x, *lre, *lim, *ldt, *dskip, *pw[7];
  float* out;
  uint64_t desc;
};

__device__ __align__(1024) uint4 g_hsT[1152 * SEQ / 8];
__device__ __align__(1024) uint4 g_xn[16 * 9 * 1024];
__device__ __align__(1024) uint4 g_z[16 * 9 * 1024];
__device__ __align__(1024) uint4 g_z7[16 * 8 * 1024];
__device__ __align__(1024) float4 g_state[9 * 32 * 32];
constexpr int SY_EPOCH = 0, SY_XN = 160, SY_HS = SY_XN + 16 * 32, SY_Z = SY_HS + 32 * 32;
__device__ __align__(1024) uint32_t g_sync[SY_Z + 32 * 32];
#define TR(role, idx)
#define TRC(idx)
#define TRG(idx)
DEVI void tr_dump() {}

DEVI uint32_t smem_u32(const void* p) { return (uint32_t)__cvta_generic_to_shared(p); }
DEVI void mbar_init(uint32_t bar, uint32_t cnt) { asm volatile("mbarrier.init.shared::cta.b64 [%0], %1;" :: "r"(bar), "r"(cnt)); }
DEVI void mbar_expect(uint32_t bar, uint32_t bytes) { asm volatile("mbarrier.arrive.expect_tx.shared::cta.b64 _, [%0], %1;" :: "r"(bar), "r"(bytes) : "memory"); }
DEVI void mbar_arrive(uint32_t bar) { asm volatile("mbarrier.arrive.shared::cta.b64 _, [%0];" :: "r"(bar) : "memory"); }
DEVI void mbar_arrive_warp(uint32_t bar) {
  asm volatile("{\n.reg .pred p;\nelect.sync _|p, 0xffffffff;\n@p mbarrier.arrive.shared::cta.b64 _, [%0];\n}" :: "r"(bar) : "memory");
}
DEVI void mbar_arrive_warp_if(uint32_t bar, int f) {
  asm volatile("{\n.reg .pred p, q;\nelect.sync _|p, 0xffffffff;\nsetp.ne.and.b32 q, %1, 0, p;\n@q mbarrier.arrive.shared::cta.b64 _, [%0];\n}" :: "r"(bar), "r"(f) : "memory");
}
DEVI void mbar_arrive2(uint32_t bar, uint32_t rbar, uint32_t o, int f = 1) {
  asm volatile("{\n.reg .pred p, q;\nelect.sync _|p, 0xffffffff;\nsetp.ne.and.b32 q, %2, 0, p;\n@q mbarrier.arrive.shared::cta.b64 _, [%0];\n"
               "@q mbarrier.arrive.shared::cluster.b64 _, [%1];\n}" :: "r"(bar + o), "r"(rbar + o), "r"(f) : "memory");
}
DEVI void mbar_wait(uint32_t& c, uint32_t bar, uint32_t parity) {
  asm volatile("{\n.reg .pred p, q;\nLW:\nadd.u32 %0, %0, 1;\nsetp.lt.u32 q, %0, %3;\n"
               "mbarrier.try_wait.parity.shared::cta.b64 p, [%1], %2;\nnot.pred p, p;\nand.pred p, p, q;\n@p bra LW;\n}"
               : "+&r"(c) : "r"(bar), "r"(parity), "n"(SPIN_MAX) : "memory");
}
DEVI void spin_check(uint32_t c) { asm volatile("{\n.reg .pred p;\nsetp.ge.u32 p, %0, %1;\n@p trap;\n}" :: "r"(c), "n"(SPIN_MAX)); }
DEVI bool elect() { uint32_t p; asm volatile("{\n.reg .pred p;\nelect.sync _|p, 0xffffffff;\nselp.u32 %0, 1, 0, p;\n}" : "=r"(p)); return p; }
DEVI void poll_ge(const uint32_t* p, uint32_t target) {
  asm volatile("{\n.reg .pred p;\n.reg .u32 c, v;\nmov.u32 c, 0;\nLW:\n"
               "ld.relaxed.gpu.global.u32 v, [%0];\nsub.u32 v, v, %1;\nsetp.ge.s32 p, v, 0;\n@p bra LD;\n"
               "nanosleep.u32 40;\nadd.u32 c, c, 1;\nsetp.gt.u32 p, c, 2000000;\n@p trap;\nbra LW;\nLD:\n}" :: "l"(p), "r"(target) : "memory");
}
DEVI void fence_gpu() { asm volatile("fence.acq_rel.gpu;" ::: "memory"); }
DEVI void fence_async_all() { asm volatile("fence.proxy.async;" ::: "memory"); }
DEVI void fence_async_smem() { asm volatile("fence.proxy.async.shared::cta;" ::: "memory"); }
DEVI void red_inc(uint32_t* p) { asm volatile("red.relaxed.gpu.global.add.u32 [%0], 1;" :: "l"(p) : "memory"); }
DEVI void st_relaxed(uint32_t* p, uint32_t v) { asm volatile("st.relaxed.gpu.global.u32 [%0], %1;" :: "l"(p), "r"(v) : "memory"); }
DEVI uint32_t ld_relaxed(const uint32_t* p) { uint32_t v; asm volatile("ld.relaxed.gpu.global.u32 %0, [%1];" : "=r"(v) : "l"(p) : "memory"); return v; }
DEVI void tma2d(uint32_t dst, const CUtensorMap* m, uint32_t bar, int c0, int c1) {
  asm volatile("cp.async.bulk.tensor.2d.shared::cluster.global.mbarrier::complete_tx::bytes [%0], [%1, {%3, %4}], [%2];"
               :: "r"(dst), "l"(m), "r"(bar), "r"(c0), "r"(c1) : "memory");
}
DEVI void tma2d_mc(uint32_t dst, const CUtensorMap* m, uint32_t bar, int c0, int c1) {
  asm volatile("cp.async.bulk.tensor.2d.shared::cluster.global.mbarrier::complete_tx::bytes.multicast::cluster [%0], [%1, {%3, %4}], [%2], %5;"
               :: "r"(dst), "l"(m), "r"(bar), "r"(c0), "r"(c1), "h"((uint16_t)3) : "memory");
}
DEVI void tma_x(uint32_t dst, const CUtensorMap* m, uint32_t bar, int col, int seg) {
  asm volatile("cp.async.bulk.tensor.5d.shared::cluster.global.mbarrier::complete_tx::bytes [%0], [%1, {%3, %5, %5, %5, %4}], [%2];"
               :: "r"(dst), "l"(m), "r"(bar), "r"(col), "r"(seg), "r"(0) : "memory");
}
DEVI void pf_l2(const void* p) { asm volatile("prefetch.global.L2 [%0];" :: "l"(p) : "memory"); }
DEVI void bulk_ld(uint32_t dst, const void* src, uint32_t bytes, uint32_t bar) {
  asm volatile("cp.async.bulk.shared::cluster.global.mbarrier::complete_tx::bytes [%0], [%1], %2, [%3];" :: "r"(dst), "l"(src), "r"(bytes), "r"(bar) : "memory");
}
DEVI void bulk_st(void* dst, uint32_t src, uint32_t bytes) {
  asm volatile("cp.async.bulk.global.shared::cta.bulk_group [%0], [%1], %2;" :: "l"(dst), "r"(src), "r"(bytes) : "memory");
}
DEVI void bulk_red(void* dst, uint32_t src, uint32_t bytes) {
  asm volatile("cp.reduce.async.bulk.global.shared::cta.bulk_group.add.noftz.bf16 [%0], [%1], %2;" :: "l"(dst), "r"(src), "r"(bytes) : "memory");
}
DEVI void wg_fence() { asm volatile("wgmma.fence.sync.aligned;" ::: "memory"); }
DEVI void mbar_wait_f(uint32_t& c, uint32_t bar, uint32_t parity) { mbar_wait(c, bar, parity); wg_fence(); }
DEVI void wg_commit() { asm volatile("wgmma.commit_group.sync.aligned;" ::: "memory"); }
template <int N> DEVI void wg_wait() { asm volatile("wgmma.wait_group.sync.aligned %0;" :: "n"(N) : "memory"); }
template <int N> DEVI void pin(float (&a)[N]) {
#pragma unroll
  for (int i = 0; i < N; i++) asm volatile("" : "+f"(a[i]) :: "memory");
}
template <int N> DEVI void pinu(uint32_t (&a)[N]) {
#pragma unroll
  for (int i = 0; i < N; i++) asm volatile("" : "+r"(a[i]) :: "memory");
}
constexpr uint64_t DESC0 = (512ull << 16) | (0x40000040ull << 32);
DEVI uint32_t pack2(float lo, float hi) { uint32_t r; asm("cvt.rn.bf16x2.f32 %0, %1, %2;" : "=r"(r) : "f"(hi), "f"(lo)); return r; }
DEVI uint32_t hmul2(uint32_t a, uint32_t b) { uint32_t r; asm("mul.rn.bf16x2 %0, %1, %2;" : "=r"(r) : "r"(a), "r"(b)); return r; }
DEVI uint32_t hadd2(uint32_t a, uint32_t b) { uint32_t r; asm("add.rn.bf16x2 %0, %1, %2;" : "=r"(r) : "r"(a), "r"(b)); return r; }
DEVI uint32_t hfma2(uint32_t a, uint32_t b, uint32_t c) { uint32_t r; asm("fma.rn.bf16x2 %0, %1, %2, %3;" : "=r"(r) : "r"(a), "r"(b), "r"(c)); return r; }
DEVI float blo(uint32_t v) { return __uint_as_float(v << 16); }
DEVI float bhi(uint32_t v) { return __uint_as_float(v & 0xffff0000u); }
DEVI float bround(float f) { return __bfloat162float(__float2bfloat16_rn(f)); }
DEVI void mma16816(float (&d)[4], uint32_t a0, uint32_t a1, uint32_t a2, uint32_t a3, uint32_t b0, uint32_t b1) {
  asm volatile("mma.sync.aligned.m16n8k16.row.col.f32.bf16.bf16.f32 {%0,%1,%2,%3}, {%4,%5,%6,%7}, {%8,%9}, {%0,%1,%2,%3};"
               : "+f"(d[0]), "+f"(d[1]), "+f"(d[2]), "+f"(d[3]) : "r"(a0), "r"(a1), "r"(a2), "r"(a3), "r"(b0), "r"(b1));
}
DEVI void ldsm4(uint32_t* r, uint32_t addr) {
  asm volatile("ldmatrix.sync.aligned.m8n8.x4.shared.b16 {%0,%1,%2,%3}, [%4];" : "=r"(r[0]), "=r"(r[1]), "=r"(r[2]), "=r"(r[3]) : "r"(addr) : "memory");
}
DEVI void stsm4(uint32_t addr, const uint32_t* r) {
  asm volatile("stmatrix.sync.aligned.m8n8.x4.shared.b16 [%4], {%0,%1,%2,%3};" :: "r"(r[0]), "r"(r[1]), "r"(r[2]), "r"(r[3]), "r"(addr) : "memory");
}
template <int I> struct IC { static constexpr int v = I; };
template <int I, int N, class Fn> DEVI void sfor(Fn&& f) { if constexpr (I < N) { f(IC<I>{}); sfor<I + 1, N>(f); } }

struct Scan {
  float lr[2], li[2];
  float cr[2], ci[2];
  float pr[2], pi[2];
  float hr[2], hi[2];
};
constexpr int W_Q = 0, W_F = 4, W_G = 8, W_L = 16;
DEVI float uf(uint32_t v) { return __uint_as_float(v); }
DEVI uint32_t fu(float v) { return __float_as_uint(v); }
DEVI void csq(float& r, float& i) { float t = r * i; r = fmaf(r, r, -i * i); i = t + t; }
DEVI void cmul(float& r, float& i, float ar, float ai) { float t = fmaf(r, ar, -i * ai); i = fmaf(r, ai, i * ar); r = t; }

DEVI void scan_params(uint32_t dst, float a, float b, float ldt) {
  const float dt = bround(expf(ldt));
  const float e = expf(dt * a);
  float sn, cs; sincosf(dt * b, &sn, &cs);
  const float lr = e * cs, li = e * sn, nr = lr - 1.0f;
  const bool sw = fabsf(a) >= fabsf(b);
  const float big = sw ? a : b, sml = sw ? b : a, t = sml / big, d = 2.0f / fmaf(sml, t, big);
  const float cr = (sw ? fmaf(li, t, nr) : fmaf(nr, t, li)) * d, ci = (sw ? fmaf(-nr, t, li) : fmaf(li, t, -nr)) * d;
  asm volatile("st.shared.v4.f32 [%0], {%1,%2,%3,%4};" :: "r"(dst), "f"(lr), "f"(li), "f"(cr), "f"(ci) : "memory");
  __syncwarp();
}
DEVI void scan_load(Scan& s, uint32_t src) {
#pragma unroll
  for (int c = 0; c < 2; c++)
    asm volatile("ld.shared.v4.f32 {%0,%1,%2,%3}, [%4];" : "=f"(s.lr[c]), "=f"(s.li[c]), "=f"(s.cr[c]), "=f"(s.ci[c]) : "r"(src + 128 * c) : "memory");
}
DEVI uint64_t fresh(uint64_t d, uint32_t c) { return d + (c >> 24); }
DEVI uint32_t ld_epoch() { uint32_t l; asm volatile("mov.u32 %0, %%laneid;" : "=r"(l)); return ld_relaxed(&g_sync[SY_EPOCH + blockIdx.x + (l >> 5)]) + 1; }
DEVI uint32_t tid_x() { uint32_t v; asm volatile("mov.u32 %0, %%tid.x;" : "=r"(v)); return v; }
template <int T0, int T1> DEVI void scan_p1(Scan& s, const float (&ur)[32], const float (&ui)[32]) {
#pragma unroll
  for (int t = T0; t < T1; t++)
#pragma unroll
    for (int c = 0; c < 2; c++) {
      const int a = 4 * (t >> 1) + 2 * c + (t & 1);
      if (t == 0) { s.hr[c] = ur[a]; s.hi[c] = ui[a]; }
      else {
        const float tr = fmaf(s.lr[c], s.hr[c], ur[a]), ti = fmaf(s.lr[c], s.hi[c], ui[a]);
        const float nr = fmaf(-s.li[c], s.hi[c], tr); s.hi[c] = fmaf(s.li[c], s.hr[c], ti); s.hr[c] = nr;
      }
    }
}
DEVI void scan_pow16(Scan& s) {
  pin(s.lr); pin(s.li);
#pragma unroll
  for (int c = 0; c < 2; c++) { s.pr[c] = s.lr[c]; s.pi[c] = s.li[c]; csq(s.pr[c], s.pi[c]); csq(s.pr[c], s.pi[c]); csq(s.pr[c], s.pi[c]); csq(s.pr[c], s.pi[c]); }
}
DEVI void scan_quad(Scan& s, uint32_t* w, float4* dst, int q, uint32_t tag) {
#pragma unroll
  for (int c = 0; c < 2; c++) {
    float r = __shfl_up_sync(0xffffffffu, s.hr[c], 1, 4), i = __shfl_up_sync(0xffffffffu, s.hi[c], 1, 4);
    if (q < 1) { r = 0.f; i = 0.f; }
    s.hr[c] = fmaf(s.pr[c], r, fmaf(-s.pi[c], i, s.hr[c])); s.hi[c] = fmaf(s.pr[c], i, fmaf(s.pi[c], r, s.hi[c]));
    w[W_Q + 2 * c] = fu((q & 1) ? s.pr[c] : 1.f); w[W_Q + 2 * c + 1] = fu((q & 1) ? s.pi[c] : 0.f);
    csq(s.pr[c], s.pi[c]);
    r = __shfl_up_sync(0xffffffffu, s.hr[c], 2, 4); i = __shfl_up_sync(0xffffffffu, s.hi[c], 2, 4);
    if (q < 2) { r = 0.f; i = 0.f; }
    s.hr[c] = fmaf(s.pr[c], r, fmaf(-s.pi[c], i, s.hr[c])); s.hi[c] = fmaf(s.pr[c], i, fmaf(s.pi[c], r, s.hi[c]));
  }
  if (q == 3) asm volatile("st.relaxed.gpu.global.v4.b32 [%0], {%1,%2,%3,%4};" :: "l"(dst), "r"((fu(s.hr[0]) & ~1u) | tag), "r"(fu(s.hi[0])), "r"(fu(s.hr[1])), "r"(fu(s.hi[1])) : "memory");
}
DEVI void scan_excl(Scan& s, uint32_t* w, int q) {
#pragma unroll
  for (int c = 0; c < 2; c++) {
    const float r = __shfl_up_sync(0xffffffffu, s.hr[c], 1, 4), i = __shfl_up_sync(0xffffffffu, s.hi[c], 1, 4);
    s.hr[c] = q < 1 ? 0.f : r; s.hi[c] = q < 1 ? 0.f : i;
    float qr = uf(w[W_Q + 2 * c]), qi = uf(w[W_Q + 2 * c + 1]);
    if (q & 2) cmul(qr, qi, s.pr[c], s.pi[c]);
    w[W_Q + 2 * c] = fu(qr); w[W_Q + 2 * c + 1] = fu(qi);
    csq(s.pr[c], s.pi[c]);
  }
}
DEVI void scan_powf(Scan& s, uint32_t* w, int q) {
#pragma unroll
  for (int c = 0; c < 2; c++) {
    float r = s.pr[c], i = s.pi[c]; csq(r, i); csq(r, i); csq(r, i);
    float fr = (q & 1) ? 1.f : r, fi = (q & 1) ? 0.f : i;
    csq(r, i);
    if (!(q & 2)) cmul(fr, fi, r, i);
    w[W_F + 2 * c] = fu(fr); w[W_F + 2 * c + 1] = fu(fi);
  }
}
template <int H, int L = W_L> DEVI void scan_reld(uint32_t* w, const float4* st, int p0, int q) {
  asm volatile("" : "+l"(st), "+r"(p0));
  st += (8 * q - 32) * 32;
#pragma unroll
  for (int k = 0; k < 4; k++) {
    uint32_t* v = w + L + 4 * k;
    asm volatile("{\n.reg .pred p;\nsetp.ge.s32 p, %5, %6;\n@p ld.relaxed.gpu.global.v4.u32 {%0,%1,%2,%3}, [%4];\n}"
                 : "+r"(v[0]), "+r"(v[1]), "+r"(v[2]), "+r"(v[3]) : "l"(st + (4 * H + k) * 32), "r"(p0), "r"(-4 * H - k) : "memory");
  }
}
template <int H, int L = W_L> DEVI void scan_gld(uint32_t* w, const float4* st, int p0, int q, uint32_t tag) {
#pragma unroll
  for (int k = 0; k < 16; k++) w[L + k] = k & 3 ? 0 : tag;
  scan_reld<H, L>(w, st, p0, q);
}
template <int H, int L = W_L> DEVI void scan_chk(uint32_t& c, uint32_t* w, const float4* st, int p0, int q, uint32_t tag) {
#pragma unroll 1
  while (__any_sync(0xffffffffu, ((w[L] ^ tag) | (w[L + 4] ^ tag) | (w[L + 8] ^ tag) | (w[L + 12] ^ tag)) & 1) && ++c < SPIN_MAX) scan_reld<H, L>(w, st, p0, q);
}
template <int H, int L = W_L> DEVI void scan_horner(Scan& s, uint32_t* w) {
#pragma unroll
  for (int k = 0; k < 4; k++)
#pragma unroll
    for (int c = 0; c < 2; c++) {
      const float vr = uf(w[L + 4 * k + 2 * c]), vi = uf(w[L + 4 * k + 2 * c + 1]);
      const float gr = uf(w[W_G + 2 * c]), gi = uf(w[W_G + 2 * c + 1]);
      if (H == 0 && k == 0) { w[W_G + 2 * c] = fu(vr); w[W_G + 2 * c + 1] = fu(vi); }
      else { w[W_G + 2 * c] = fu(fmaf(s.pr[c], gr, fmaf(-s.pi[c], gi, vr))); w[W_G + 2 * c + 1] = fu(fmaf(s.pr[c], gi, fmaf(s.pi[c], gr, vi))); }
    }
}
DEVI void scan_carry(Scan& s, uint32_t* w) {
#pragma unroll
  for (int c = 0; c < 2; c++) {
    float gr = uf(w[W_G + 2 * c]), gi = uf(w[W_G + 2 * c + 1]);
    const float qr = uf(w[W_Q + 2 * c]), qi = uf(w[W_Q + 2 * c + 1]);
    cmul(gr, gi, uf(w[W_F + 2 * c]), uf(w[W_F + 2 * c + 1]));
    gr += __shfl_xor_sync(0xffffffffu, gr, 1); gi += __shfl_xor_sync(0xffffffffu, gi, 1);
    gr += __shfl_xor_sync(0xffffffffu, gr, 2); gi += __shfl_xor_sync(0xffffffffu, gi, 2);
    s.hr[c] = fmaf(qr, gr, fmaf(-qi, gi, s.hr[c])); s.hi[c] = fmaf(qr, gi, fmaf(qi, gr, s.hi[c]));
  }
}
template <int JJ> DEVI void scan_p2(Scan& s, uint32_t (&keep)[4], const float (&ur)[32], const float (&ui)[32], uint32_t* dst, bool odd) {
#pragma unroll
  for (int c = 0; c < 2; c++) {
    float o_r[2], o_i[2];
#pragma unroll
    for (int e = 0; e < 2; e++) {
      const int a = 4 * JJ + 2 * c + e;
      const float tr = fmaf(s.lr[c], s.hr[c], ur[a]), ti = fmaf(s.lr[c], s.hi[c], ui[a]);
      const float nr = fmaf(-s.li[c], s.hi[c], tr); s.hi[c] = fmaf(s.li[c], s.hr[c], ti); s.hr[c] = nr;
      o_r[e] = fmaf(s.cr[c], s.hr[c], -s.ci[c] * s.hi[c]); o_i[e] = fmaf(-s.cr[c], s.hi[c], -s.ci[c] * s.hr[c]);
    }
#pragma unroll
    for (int m = 0; m < 2; m++) {
      const uint32_t v = m ? pack2(o_i[0], o_i[1]) : pack2(o_r[0], o_r[1]);
      if constexpr ((JJ & 1) == 0) keep[2 * c + m] = v;
      else {
        const uint32_t k = keep[2 * c + m], rv = __shfl_xor_sync(0xffffffffu, odd ? k : v, 1);
        asm volatile("st.global.v2.b32 [%0], {%1,%2};" :: "l"(dst + (m * DM + c * 8) * (SEQ / 2) + 4 * (JJ - 1)), "r"(odd ? rv : k), "r"(odd ? v : rv) : "memory");
      }
    }
  }
}
DEVI void pin_s(Scan& s) { pin(s.hr); pin(s.hi); pin(s.pr); pin(s.pi); }
template <int A, int N> DEVI void pin_w(uint32_t* w) {
#pragma unroll
  for (int i = A; i < A + N; i++) asm volatile("" : "+r"(w[i]) :: "memory");
}

DEVI float silu_h(float v) {
  float t;
  asm("tanh.approx.f32 %0, %1;" : "=f"(t) : "f"(v));
  return fmaf(v, t, v);
}
template <int A0, int A1> DEVI void epi_silu(float (&z)[32], const uint32_t (&zr)[16]) {
#pragma unroll
  for (int a = A0; a < A1; a++) {
    z[a] = silu_h(z[a] + ((a & 1) ? bhi(zr[a >> 1]) : blo(zr[a >> 1])));
    asm volatile("" : "+f"(z[a]) :: "memory");
  }
}
template <int JJ, bool MUL> DEVI void epi_x(float (&t)[32], const uint32_t* dh, uint32_t xa) {
  uint32_t xv[4];
  ldsm4(xv, xa ^ (JJ << 4));
#pragma unroll
  for (int p = 0; p < 4; p++) {
    if constexpr (MUL) xv[p] = hmul2(xv[p], dh[JJ + (p >> 1)]);
    const int a = 4 * JJ + 2 * p;
    t[a] = blo(xv[p]); t[a + 1] = bhi(xv[p]);
    asm volatile("" : "+f"(t[a]), "+f"(t[a + 1]) :: "memory");
  }
}
DEVI void epi_store(float* o, const float (&t)[32], const float (&g)[32], const float (&y)[32]) {
#pragma unroll
  for (int jj = 0; jj < 8; jj++)
#pragma unroll
    for (int r = 0; r < 2; r++) {
      const int a = 4 * jj + 2 * r;
      asm volatile("st.global.v2.f32 [%0], {%1,%2};" :: "l"(o + r * 2 * DM + 8 * jj), "f"(fmaf(g[a], y[a], t[a])), "f"(fmaf(g[a + 1], y[a + 1], t[a + 1])) : "memory");
    }
}
DEVI void ldg4(uint32_t* r, const void* p) {
  asm volatile("ld.relaxed.gpu.global.v4.u32 {%0,%1,%2,%3}, [%4];" : "=r"(r[0]), "=r"(r[1]), "=r"(r[2]), "=r"(r[3]) : "l"(p) : "memory");
}
DEVI void lds4(uint32_t* r, uint32_t addr) {
  asm volatile("ld.shared.v4.b32 {%0,%1,%2,%3}, [%4];" : "=r"(r[0]), "=r"(r[1]), "=r"(r[2]), "=r"(r[3]) : "r"(addr) : "memory");
}
DEVI int blk_of(int j, int b) { return b == 0 ? 8 : ((j + b) & 7); }

constexpr uint32_t UNIT = 24576;
#define NC1 6
#define ZT 21
#define ZN 3
#define ZK 4
constexpr int PFP = 400;
#define STAG 1
#define PFX 1
struct Ring { uint32_t o, ph; };
DEVI void ring_next(Ring& r) { r.o += 8; if (r.o == 40) { r.o = 0; r.ph ^= 1; } }

DEVI void spare_consumer(const Params& P, uint32_t sb, int warp, int lane) {
  const uint32_t tag = ld_epoch() & 1;
  const int wg = warp >> 2, w = warp & 3, g = lane >> 2, q = lane & 3, sp = blockIdx.x - 128;
  const uint32_t bar = sb + OFF_BAR, rb = bar + 40 * wg;
  const uint64_t d0 = P.desc + ((sb & 0x3FFFF) >> 4), dr = d0 + 9 * 1024 + wg * 512;
  uint32_t c = 0, prev = 0;
  Ring rg = {0, 0};
  Scan s;
  scan_load(s, sb + OFF_PAR + (16 * w + g) * 16);
  if (wg) asm volatile("bar.sync 1, 256;" ::: "memory");
  mbar_wait(c, bar + 8 * B_RES, 0);
#pragma unroll 1
  for (int r = 0; r < 4; r++) {
    float ur[32], ui[32];
    uint32_t wk[48], keep[4];
#pragma unroll 1
    for (int u = 0; u < 9; u++) {
      mbar_wait(c, rb + 8 * B_FULL + rg.o, rg.ph);
      wg_fence();
      const uint64_t a = d0 + u * 1024, b = dr + rg.o * 128;
      wg_ss64p<0, 0, 0, 0>(ur, a, b, u); wg_ss64p<0, 0, 512, 0>(ui, a, b, u);
      sfor<1, 4>([&](auto K) { wg_ss64<0, 0, 2 * K.v, 2 * K.v>(ur, a, b); wg_ss64<0, 0, 512 + 2 * K.v, 2 * K.v>(ui, a, b); });
      wg_commit();
      wg_wait<1>();
      mbar_arrive_warp_if(rb + 8 * B_EMPTY + prev, u);
      prev = rg.o;
      ring_next(rg);
    }
    wg_wait<0>();
    mbar_arrive_warp(rb + 8 * B_EMPTY + prev);
    mbar_arrive_warp_if(bar + 8 * B_XN, r == 3);
    if (r + wg == 0) asm volatile("bar.arrive 1, 256;" ::: "memory");
    pin(ur); pin(ui);
    TRC(1 + 4 * r);
    const int seg = 8 * r + 4 * wg + sp;
    float4* stp = g_state + 8 * 1024 + seg * 32 + w * 8 + g;
    uint32_t* hsp = (uint32_t*)g_hsT + (size_t)(512 + 16 * w + g) * (SEQ / 2) + seg * 32 + (q & 1) * 4 + (q & 2);
    scan_pow16(s);
    scan_p1<0, 16>(s, ur, ui);
    scan_quad(s, wk, stp, q, tag);
    scan_gld<0>(wk, stp, seg - 32 + 8 * q, q, tag);
    scan_excl(s, wk, q); scan_powf(s, wk, q);
    scan_gld<1, 32>(wk, stp, seg - 32 + 8 * q, q, tag);
    TRC(2 + 4 * r);
    scan_chk<0>(c, wk, stp, seg - 32 + 8 * q, q, tag); scan_horner<0>(s, wk);
    scan_chk<1, 32>(c, wk, stp, seg - 32 + 8 * q, q, tag); scan_horner<1, 32>(s, wk);
    TRC(3 + 4 * r);
    scan_carry(s, wk);
#pragma unroll 1
    for (int k = 0; k < 4; k++, hsp += 8) {
      scan_p2<0>(s, keep, ur, ui, hsp, q & 1); scan_p2<1>(s, keep, ur, ui, hsp, q & 1);
#pragma unroll
      for (int i = 0; i < 24; i++) { ur[i] = ur[i + 8]; ui[i] = ui[i + 8]; }
    }
    __syncwarp(); mbar_arrive_warp(bar + 8 * (B_HS + wg));
    TRC(4 + 4 * r);
  }
  float y[4][32];
  rg.o = 0; rg.ph = 0;
#pragma unroll 1
  for (int u = 0; u < 18; u++) {
    mbar_wait(c, bar + 8 * B_XT + rg.o, rg.ph);
    wg_fence();
    const uint64_t b = d0 + rg.o * 576, a = b + wg * 512;
    sfor<0, 4>([&](auto R) {
      constexpr uint32_t o = R.v * 1024;
      wg_ss64p<1, 0, o, 4096>(y[R.v], a, b, u); wg_ss64<1, 0, o + 128, 4098>(y[R.v], a, b); wg_ss64<1, 0, o + 256, 4100>(y[R.v], a, b); wg_ss64<1, 0, o + 384, 4102>(y[R.v], a, b);
    });
    wg_commit();
    wg_wait<0>();
    mbar_arrive_warp(bar + 8 * (B_XN + 1) + rg.o);
    rg.o += 8; if (rg.o == 24) { rg.o = 0; rg.ph ^= 1; }
  }
  TRC(22);
  uint32_t dh[8], lsm = sb + wg * 8192 + (16 * w + (lane & 15)) * 128 + (((lane >> 4) ^ (lane & 7)) << 4), za = sb + 147456 + warp * 2048 + lane * 16;
  float* op = P.out + (size_t)((4 * wg + sp) * 64 + 16 * (g >> 1) + 4 * w + (g & 1)) * DM + 2 * q + 512;
  lds4(dh, sb + OFF_D + q * 32); lds4(dh + 4, sb + OFF_D + q * 32 + 16);
#pragma unroll
  for (int k = 0; k < 3; k++) mbar_wait(c, bar + 8 * (B_XT + k), 0);
#pragma unroll
  for (int r = 0; r < 4; r++) pin(y[r]);
#pragma unroll 1
  for (int r = 0; r < 4; r++, lsm += SLOT, za += SLOT, op += 512 * DM) {
    float t[32], z[32];
    uint32_t zr[16];
#pragma unroll
    for (int k = 0; k < 4; k++) lds4(&zr[4 * k], za + k * 512);
    sfor<0, 4>([&](auto K) { epi_x<2 * K.v, true>(t, dh, lsm); });
#pragma unroll
    for (int k = 0; k < 32; k++) { y[0][k] += t[k]; z[k] = silu_h(k & 1 ? bhi(zr[k >> 1]) : blo(zr[k >> 1])); }
    sfor<0, 4>([&](auto K) { epi_x<2 * K.v, false>(t, nullptr, lsm + 73728); });
    epi_store(op, t, z, y[0]);
#pragma unroll
    for (int k = 0; k < 96; k++) y[k >> 5][k & 31] = y[(k >> 5) + 1][k & 31];
  }
  TRC(23);
  spin_check(c);
}

template <int T, int R0 = 0, int R1 = 16> DEVI void tile_end(uint32_t (&h)[144], float (&acc)[64]) {
  if constexpr (R0 == 0) pin(acc);
#pragma unroll
  for (int r = R0; r < R1; r++) {
    h[16 * T + r] = pack2(acc[2 * r] * acc[32 + 2 * r] * 0.5f, acc[2 * r + 1] * acc[33 + 2 * r] * 0.5f);
    asm volatile("" : "+r"(h[16 * T + r]) :: "memory");
  }
}

#define IDS const int tx = tid_x(), lane = tx & 31, warp = tx >> 5, w = warp & 3, g = lane >> 2, q = lane & 3; (void)w; (void)g; (void)q
DEVI void main_consumer(const Params& P, uint32_t sb, int wg) {
  const uint32_t bar = sb + OFF_BAR;
  const int j = CJ(blockIdx.x), mi = CM(blockIdx.x);
  uint32_t rbar;
  asm("mapa.shared::cluster.u32 %0, %1, %2;" : "=r"(rbar) : "r"(bar), "r"(~blockIdx.x & 1));
  uint64_t d0 = P.desc + ((sb & 0x3FFFF) >> 4), dx = d0 + wg * 512;
  uint32_t c = 0, h[144];
  Ring rg = {32, 1};
  uint32_t prev = 24;
  {
    float acc[64];
    Scan s;
    {
      IDS;
      constexpr int NKEEP = 8;
      uint32_t xv[144], one[8];
      float d[2][4][4];
#pragma unroll
      for (int k = 0; k < 32; k++) (&d[0][0][0])[k] = 0.f;
#pragma unroll
      for (int k = 0; k < 8; k++) one[k] = __shfl_sync(0xffffffffu, lane < 8 ? 0x3f803f80u : 0u, k);
      const uint32_t la = sb + (16 * warp + (lane & 7) + 8 * (lane >> 4)) * 128 + ((((lane >> 3) & 1) ^ (lane & 7)) << 4);
      const uint32_t sa = sb + (16 * warp + (lane & 15)) * 128 + (((lane >> 4) ^ (lane & 7)) << 4);
#pragma unroll
      for (int u = 0; u < 9; u++) {
        if (u % 3 == 0) { mbar_wait(c, bar + 8 * (B_X0 + u / 3) + 24 * wg, 0); TRC(144 + u / 3); }
#pragma unroll
        for (int k = 0; k < 4; k++) ldsm4(&xv[16 * u + 4 * k], (la ^ (k << 5)) + u * SLOT);
#pragma unroll
        for (int k = 0; k < 4; k++)
#pragma unroll
          for (int r = 0; r < 2; r++) {
            const uint32_t v0 = xv[16 * u + 4 * k + 2 * r], v1 = xv[16 * u + 4 * k + 2 * r + 1];
            mma16816(d[r][k], v0, one[4 * r + 2 * (k & 1)], v1, one[4 * r + 2 * (k & 1) + 1], v0, v1);
          }
      }
      mbar_wait(c, bar + 8 * B_FULL, 0);
      TRC(140);
      const int src = 4 * g + (g >> 1);
      uint32_t rh2[2], rl2[2], c2[2];
#pragma unroll
      for (int r = 0; r < 2; r++) {
#pragma unroll
        for (int k = 0; k < 4; k++) d[r][0][k] = (d[r][0][k] + d[r][1][k]) + (d[r][2][k] + d[r][3][k]);
        float ss = (g & 1) ? d[r][0][1] : d[r][0][0], sm = (g & 1) ? d[r][0][3] : d[r][0][2];
        ss = __shfl_sync(0xffffffffu, ss, src); sm = __shfl_sync(0xffffffffu, sm, src);
        const float mean = sm * (1.0f / DM);
        const float var = fmaxf(fmaf(-mean, mean, ss * (1.0f / DM)), 0.f);
        float sd, rs;
        asm("sqrt.approx.f32 %0, %1;" : "=f"(sd) : "f"(bhi(pack2(0.f, bhi(pack2(0.f, var)) + 1e-5f))));
        asm("rcp.approx.f32 %0, %1;" : "=f"(rs) : "f"(bhi(pack2(0.f, sd))));
        rh2[r] = pack2(rs, rs);
        const float rl = rs - bhi(rh2[r]), cc = -bhi(pack2(0.f, mean)) * rs;
        rl2[r] = pack2(rl, rl); c2[r] = pack2(cc, cc);
      }
      auto norm = [&](auto U) {
#pragma unroll
        for (int k = 0; k < 4; k++) {
          uint32_t* v = &xv[16 * U.v + 4 * k];
          const uint32_t t1 = U.v < NKEEP ? v[2] : v[1], t2 = U.v < NKEEP ? v[1] : v[2];
          v[0] = hfma2(v[0], rh2[0], hfma2(v[0], rl2[0], c2[0])); v[1] = hfma2(t1, rh2[1], hfma2(t1, rl2[1], c2[1]));
          v[2] = hfma2(t2, rh2[0], hfma2(t2, rl2[0], c2[0])); v[3] = hfma2(v[3], rh2[1], hfma2(v[3], rl2[1], c2[1]));
          stsm4((sa ^ (k << 5)) + U.v * SLOT, v);
        }
      };
      norm(IC<0>{});
      TRC(0); TRG(160);
      sfor<0, 9>([&](auto U) {
        constexpr uint32_t u = U.v, b = (9 + u % 5) * 1024;
        if constexpr (u == 5) d0 = fresh(d0, c);
        wg_fence();
        if constexpr (u == 0) wg_rs128z<1, b>(acc, &xv[16 * u], d0); else wg_rs128<1, b>(acc, &xv[16 * u], d0);
        wg_rs128<1, b + 128>(acc, &xv[16 * u + 4], d0);
        if constexpr (u + 1 >= NKEEP && u < 8) {
#pragma unroll
          for (int k = 0; k < 4; k++) ldsm4(&xv[16 * u + 16 + 4 * k], (sa ^ (k << 5)) + (u + 1) * SLOT);
        }
        if constexpr (u == 8) {
          fence_async_smem();
          if (wg == 0) asm volatile("bar.sync 1, 128;" ::: "memory"); else asm volatile("bar.sync 2, 128;" ::: "memory");
        }
        if constexpr (u == 1) mbar_arrive_warp(bar + 8 * B_XN);
        mbar_wait_f(c, bar + 8 * (B_FULL + (u + 1) % 5), ((u + 1) / 5) & 1);
        if constexpr (u < 8) norm(IC<u + 1>{});
        if constexpr (u == 8) { scan_load(s, sb + OFF_PAR + ((tid_x() & 96) * 2 + (tid_x() & 28)) * 4); scan_pow16(s); pin(s.pr); pin(s.pi); }
        wg_rs128<1, b + 256>(acc, &xv[16 * u + 8], d0);
        wg_commit();
        if constexpr (u > 0) { wg_wait<1>(); mbar_arrive2(bar, rbar, 8 * (B_EMPTY + (u - 1) % 5)); }
        wg_rs128<1, b + 384>(acc, &xv[16 * u + 12], d0);
        wg_commit();
      });
    }
    TRC(9);
    float ur[32], ui[32];
#pragma unroll 1
    for (int u = 0; u < 9; u++) {
      wg_fence();
      const uint64_t a = d0 + 9 * 1024 + rg.o * 128, b = dx + u * 1024;
      wg_ss64p<0, 0, 0, 0>(ur, a, b, u); wg_ss64p<0, 0, 512, 0>(ui, a, b, u);
      wg_ss64<0, 0, 2, 2>(ur, a, b); wg_ss64<0, 0, 514, 2>(ui, a, b);
      wg_commit();
      wg_wait<1>();
      mbar_arrive2(bar, rbar, 8 * B_EMPTY + prev);
      prev = rg.o;
      ring_next(rg);
      wg_ss64<0, 0, 4, 4>(ur, a, b); wg_ss64<0, 0, 516, 4>(ui, a, b);
      mbar_wait_f(c, bar + 8 * B_FULL + rg.o, rg.ph);
      wg_ss64<0, 0, 6, 6>(ur, a, b); wg_ss64<0, 0, 518, 6>(ui, a, b);
      wg_commit();
    }
    tile_end<0>(h, acc);
    TRC(18); TRG(161);
    IDS;
    const uint32_t tag = ld_epoch() & 1;
    const int seg = mi * 2 + wg;
    float4* stp = g_state + j * 1024 + seg * 32 + w * 8 + g;
    uint32_t* hsp = (uint32_t*)g_hsT + (size_t)(j * 64 + 16 * w + g) * (SEQ / 2) + seg * 32 + (q & 1) * 4 + (q & 2);
    uint32_t wk[32], keep[4];
    sfor<1, 4>([&](auto T) {
      constexpr int t = T.v;
      sfor<0, 9>([&](auto U) {
        constexpr uint32_t u = U.v, S = 9 + 9 * t + u, sg = S - 18, a = u * 1024, b = (9 + S % 5) * 1024;
        if constexpr (u == 0) dx = fresh(dx, c);
        if constexpr (sg % 5 == 0) d0 = fresh(d0, c);
        if constexpr (u == 0) { wg_fence(); wg_ss128p<0, 1, a, b>(acc, dx, d0, (int)P.desc & 1); }
        else wg_ss128<0, 1, a, b>(acc, dx, d0);
        wg_ss128<0, 1, a + 2, b + 128>(acc, dx, d0);
        wg_commit();
        mbar_wait_f(c, bar + 8 * (B_FULL + (S + 1) % 5), ((S + 1) / 5) & 1);
        wg_ss128<0, 1, a + 4, b + 256>(acc, dx, d0);
        wg_commit();
        if constexpr (u > 0 || t == 1) { wg_wait<2>(); mbar_arrive2(bar, rbar, 8 * (B_EMPTY + (S - 1) % 5)); }
        wg_ss128<0, 1, a + 6, b + 384>(acc, dx, d0);
        wg_commit();
        if constexpr (sg == 0) { pin(ur); pin(ui); } else pin_s(s);
        if constexpr (sg < 4) scan_p1<4 * sg, 4 * sg + 4>(s, ur, ui);
        if constexpr (sg == 4) { scan_quad(s, wk, stp, q, tag); pin_w<W_Q, 4>(wk); }
        if constexpr (sg == 5) { scan_excl(s, wk, q); pin_w<W_Q, 4>(wk); }
        if constexpr (sg == 6) { scan_powf(s, wk, q); pin_w<W_F, 4>(wk); }
        if constexpr (sg == 9) scan_gld<0>(wk, stp, seg - 32 + 8 * q, q, tag);
        if constexpr (sg == 12) {
          scan_chk<0>(c, wk, stp, seg - 32 + 8 * q, q, tag); wg_fence();
          scan_horner<0>(s, wk); pin_w<W_G, 4>(wk); scan_gld<1>(wk, stp, seg - 32 + 8 * q, q, tag);
        }
        if constexpr (sg == 15) { scan_chk<1>(c, wk, stp, seg - 32 + 8 * q, q, tag); wg_fence(); scan_horner<1>(s, wk); pin_w<W_G, 4>(wk); }
        if constexpr (sg == 16) { pin_w<W_G, 4>(wk); scan_carry(s, wk); }
        if constexpr (sg >= 18 && sg < 26) { scan_p2<sg - 18>(s, keep, ur, ui, hsp, q & 1); if constexpr (!(sg & 1)) pinu(keep); }
        if constexpr (sg == 25) { __syncwarp(); mbar_arrive_warp(bar + 8 * (B_HS + wg)); }
        if constexpr (sg < 25) pin_s(s);
      });
      wg_wait<0>();
      mbar_arrive2(bar, rbar, 8 * (B_EMPTY + (17 + 9 * t) % 5));
      tile_end<t>(h, acc);
      TRC(18 + 9 * t);
    });
  }
  TRG(162);
  rg.o = 0; rg.ph = 1;
  float y[32], z[32];
  sfor<4, 9>([&](auto T) {
    float acc[64];
    if (wg) asm volatile("bar.sync 5, 256;" ::: "memory");
#pragma unroll 1
    for (int u = 0; u < 9; u++) {
      wg_fence();
      const uint64_t a = dx + u * 1024, b = d0 + 9 * 1024 + rg.o * 128;
      wg_ss128p<0, 1, 0, 0>(acc, a, b, u); wg_ss128<0, 1, 2, 128>(acc, a, b);
      wg_commit();
      const uint32_t cur = rg.o;
      ring_next(rg);
      mbar_wait_f(c, bar + 8 * B_FULL + rg.o, rg.ph);
      wg_ss128<0, 1, 4, 256>(acc, a, b);
      wg_commit();
      wg_wait<2>();
      mbar_arrive2(bar, rbar, 8 * B_EMPTY + prev, u);
      asm volatile("{\n.reg .pred p;\nsetp.eq.b32 p, %0, %1;\n@p bar.arrive 5, 256;\n}" :: "r"(u + 16 * wg), "n"(STAG) : "memory");
      prev = cur;
      wg_ss128<0, 1, 6, 384>(acc, a, b);
      wg_commit();
    }
    wg_wait<0>();
    mbar_arrive2(bar, rbar, 8 * B_EMPTY + prev);
    tile_end<T.v>(h, acc);
    TRC(18 + 9 * T.v);
  });
  TRG(163);
  auto down = [&](auto I, uint64_t db, uint32_t bo, uint32_t ph, auto&& extra) {
    constexpr int i = I.v;
    sfor<0, 12>([&](auto K) {
      constexpr uint32_t k = K.v, ob = i * (UNIT / 16) + k * 128;
      if constexpr (k == 0 && i < 2) wg_fence();
      if constexpr (i == 0 && k == 0) wg_rs64z<1, ob>(z, &h[0], db); else wg_rs64<1, ob>(z, &h[48 * i + 4 * k], db);
      if constexpr (k == 4) {
        wg_commit();
        wg_wait<1>();
        mbar_arrive2(bar, rbar, 8 * (B_EMPTYT + ((i + 3) & 3)) + (i ? bo : bo ^ 32));
      }
      if constexpr (k == 8) mbar_wait_f(c, bar + 8 * (B_FULLT + i + 1) + bo, ph);
      if constexpr (k == 10 && i == 2) mbar_wait_f(c, bar + 8 * B_FULLT + (bo ^ 32), ph ^ (bo >> 5));
      extra(K);
    });
    wg_commit();
  };
  {
    IDS;
    const uint32_t lsm = sb + (16 * warp + (lane & 15)) * 128 + (((lane >> 4) ^ (lane & 7)) << 4);
    uint32_t dh[8];
    mbar_wait_f(c, bar + 8 * B_FULLT, 0);
    sfor<0, 12>([&](auto K) {
      constexpr uint32_t k = K.v;
      if constexpr (k == 0) wg_rs64z<1, 1024>(z, &h[0], d0); else wg_rs64<1, 1024 + k * 128>(z, &h[4 * k], d0);
      if constexpr (k == 1) { lds4(dh, sb + OFF_D + q * 32); lds4(dh + 4, sb + OFF_D + q * 32 + 16); }
      if constexpr (k == 2) mbar_wait_f(c, bar + 8 * (B_FULLT + 1), 0);
      if constexpr (k >= 3 && k < 11 && (k & 1)) epi_x<k - 3, true>(y, dh, lsm);
    });
    wg_commit();
  }
  {
    uint32_t o = 0, ph = 0;
    IDS;
    const uint32_t stg = sb + 13 * SLOT + warp * 2048 + lane * 16;
    uint4* z7 = g_z7 + (mi * 8 + ((j + 7) & 7)) * 1024 + warp * 128 + lane;
#pragma unroll 1
    for (int b = 0; b < 8; b++) {
      const uint64_t db = d0 + 1024 + o * (UNIT / 128);
      down(IC<1>{}, db, o, ph, [&](auto) {});
      down(IC<2>{}, db, o, ph, [&](auto K) { if constexpr (K.v == 6) mbar_wait_f(c, bar + 8 * (B_DF + wg), b & 1); });
      constexpr uint32_t O = 3 * (UNIT / 16);
      const uint64_t da = db + wg * 512;
      wg_ss64<1, 0, O, O + 1024>(y, da, db); wg_ss64<1, 0, O + 128, O + 1026>(y, da, db);
      wg_commit();
      wg_wait<1>();
      pin(z);
      sfor<0, 4>([&](auto K) {
        constexpr int k = K.v;
        asm volatile("{\n.reg .pred p;\nsetp.eq.b32 p, %6, 7;\n@!p st.shared.v4.b32 [%0], {%1,%2,%3,%4};\n@p st.relaxed.gpu.global.v4.b32 [%5], {%1,%2,%3,%4};\n}"
                     :: "r"(stg + k * 512), "r"(pack2(z[8 * k], z[8 * k + 1])), "r"(pack2(z[8 * k + 2], z[8 * k + 3])), "r"(pack2(z[8 * k + 4], z[8 * k + 5])),
                        "r"(pack2(z[8 * k + 6], z[8 * k + 7])), "l"(z7 + k * 32), "r"(b) : "memory");
        if constexpr (k == 1) {
          wg_ss64<1, 0, O + 256, O + 1028>(y, da, db); wg_ss64<1, 0, O + 384, O + 1030>(y, da, db);
          wg_commit();
          mbar_arrive2(bar, rbar, 8 * (B_EMPTYT + 2) + o);
        }
      });
      __syncwarp();
      mbar_arrive_warp(bar + 8 * (B_DR + wg));
      TRC(91 + b);
      ph ^= o >> 5; o ^= 32;
      down(IC<0>{}, d0 + 1024 + o * (UNIT / 128), o, ph, [&](auto) {});
    }
  }
  IDS;
  float tt[32];
  uint32_t zr[16], zl[16];
  const uint32_t lsm = sb + (16 * warp + (lane & 15)) * 128 + (((lane >> 4) ^ (lane & 7)) << 4);
  const size_t orow = (size_t)(mi * 128 + wg * 64 + 16 * (g >> 1) + 4 * w + (g & 1)) * DM + 2 * q;
  const uint4* z7 = g_z7 + (mi * 8 + j) * 1024 + warp * 128 + lane;
  sfor<33, 45>([&](auto TT) {
    constexpr int T = TT.v, i = T - NC1 - 32, nx = T + 1;
    constexpr uint32_t O = 1024 + (T & 7) * (UNIT / 16);
    if constexpr (T == 33 || T == 40) { d0 = fresh(d0, c); dx = fresh(dx, c); }
    if constexpr (i == 1 || i == 2) {
      sfor<0, 12>([&](auto K) {
        constexpr int k = K.v, n = 12 * i - 12 + k;
        wg_rs64<1, O + k * 128>(z, &h[48 * i + 4 * k], d0);
        if constexpr (k == 4) { wg_commit(); wg_wait<1>(); }
        if constexpr (k == 8) mbar_wait_f(c, bar + 8 * (B_FULLT + (nx & 7)), (nx >> 3) & 1);
        if constexpr (n == ZK) {
#pragma unroll
          for (int m = 0; m < 4; m++) ldg4(&zl[4 * m], z7 + m * 32);
        }
        if constexpr (n == 16) mbar_wait_f(c, bar + 8 * (B_XT + wg), 0);
        if constexpr (n > 16 && n <= 20) epi_x<2 * n - 34, false>(tt, nullptr, lsm);
        if constexpr (n == ZT) {
          TRC(10);
          mbar_wait_f(c, bar + 8 * (B_Z + wg), 0);
          TRC(11);
#pragma unroll
          for (int m = 0; m < 4; m++) lds4(&zr[4 * m], sb + 13 * SLOT + warp * 2048 + lane * 16 + m * 512);
        }
      });
      wg_commit();
    } else {
      wg_ss64<1, 0, O, O + 1024>(y, dx, d0); wg_ss64<1, 0, O + 128, O + 1026>(y, dx, d0);
      if constexpr (T < 38 || i == 3) { wg_commit(); wg_wait<1>(); }
      if constexpr (T < 38) mbar_arrive2(bar, rbar, 8 * (B_EMPTYT + ((T - 1) & 7)));
      if constexpr (T < 44) mbar_wait_f(c, bar + 8 * (B_FULLT + (nx & 7)), (nx >> 3) & 1);
      wg_ss64<1, 0, O + 256, O + 1028>(y, dx, d0); wg_ss64<1, 0, O + 384, O + 1030>(y, dx, d0);
      wg_commit();
    }
    if constexpr (i == 2) {
#pragma unroll 1
      while (__any_sync(0xffffffffu, zl[0] == ~0u || zl[4] == ~0u || zl[8] == ~0u || zl[12] == ~0u) && ++c < SPIN_MAX) {
#pragma unroll
        for (int m = 0; m < 4; m++) ldg4(&zl[4 * m], z7 + m * 32);
        TRC(13);
      }
      TRC(12);
      wg_fence();
#pragma unroll
      for (int m = 0; m < 16; m++) zr[m] = hadd2(zr[m], zl[m]);
      pinu(zr);
    }
    if constexpr (i == 3) pin(z);
    if constexpr (i >= 3 && i < 3 + ZN) epi_silu<(32 * (i - 3) / ZN) & ~1, (32 * (i - 2) / ZN) & ~1>(z, zr);
    if constexpr (T == 34) { TRC(99); TRG(164); TRC(13); }
  });
  wg_wait<0>();
  TRC(137);
  pin(y);
  epi_store(P.out + orow + j * 64, tt, z, y);
  TRC(138);
  TRG(253);
  spin_check(c);
}

DEVI void main_producer(const Params& P, uint32_t sb, int mi, int j) {
  const uint32_t bar = sb + OFF_BAR;
  uint32_t c = 0;
  Ring rg = {0, 1};
  if (elect()) {
    uint32_t dst = sb, fb = bar + 8 * B_X0;
#pragma unroll 1
    for (int u = 1, kb = j, n = 1; u < 18; u++, n++) {
      if (n == 3) { n = 0; fb += 8; }
      dst += u == 9 ? 8192 - 8 * SLOT : SLOT;
      if (++kb == 9) kb = 0;
      tma_x(dst, &P.xp, fb, kb * 64, 2 * mi + (u > 8));
    }
  }
  __syncwarp();
  asm volatile("barrier.cluster.wait.acquire.aligned;" ::: "memory");
  const int rk = mi & 1;
#pragma unroll 1
  for (int t = 0; t < 10; t++) {
    const CUtensorMap* m0 = t == 1 ? &P.bre : &P.wg;
    int kb = j;
#pragma unroll 1
    for (int u = 0; u < 9; u++) {
      const int c0 = t == 1 ? kb * 64 : j * DM + (t ? t - 1 : 0) * 64, c1 = t == 1 ? j * 64 : kb * 64;
      mbar_wait(c, bar + 8 * B_EMPTY + rg.o, rg.ph);
      if (elect()) {
        const uint32_t fb = bar + 8 * B_FULL + rg.o, dst = sb + 9 * SLOT + rg.o * 2048;
        mbar_expect(fb, SLOT); tma2d_mc(dst + rk * 8192, m0 + rk, fb, c0, c1);
      }
      TR(2, 9 * t + u);
      if (++kb == 9) kb = 0;
      ring_next(rg);
    }
  }
#pragma unroll 1
  for (int b = 0; b < 9; b++) {
    const int c0 = blk_of(j, b) * 64;
    sfor<0, 3>([&](auto I) {
      constexpr int i = I.v;
      const int T = 4 * b + i + (i && b == 8 ? NC1 : 0), U = T & 7;
      const uint32_t fb = bar + 8 * (B_FULLT + U), dst = sb + SLOT + U * UNIT + rk * (UNIT / 2);
      if (b > 1) mbar_wait(c, bar + 8 * (B_EMPTYT + U), ((T >> 3) - 1) & 1);
      else if (i == 2 - 2 * b) {
        mbar_wait(c, bar + 8 * (B_EMPTY + 1 + b), 1);
        mbar_arrive_warp(bar + 8 * (b ? B_P2 : B_FULL));
        if (b) { mbar_wait(c, bar + 8 * (B_EMPTY + 4), 1); mbar_arrive_warp(bar + 8 * (B_P2 + 1)); mbar_arrive_warp(bar + 8 * B_DF); mbar_arrive_warp(bar + 8 * (B_DF + 1)); }
      }
      if (elect()) { mbar_expect(fb, UNIT); tma2d_mc(dst, &P.wd, fb, c0, j * DM + i * 192 + rk * 96); }
      TR(2, 100 + T);
    });
  }
  spin_check(c);
}
DEVI void spare_producer(const Params& P, uint32_t sb, int sp, int wg, int lane, uint32_t ep) {
  const uint32_t bar = sb + OFF_BAR, rb = bar + 40 * wg, dst = sb + 9 * SLOT + wg * 8192;
  uint32_t c = 0;
  if (wg == 0 && elect()) {
    mbar_expect(bar + 8 * B_RES, 9 * SLOT);
#pragma unroll 1
    for (int u = 0; u < 18; u++) tma2d(sb + u * 8192, &P.bre + (u & 1), bar + 8 * B_RES, (u >> 1) * 64, 512);
  }
  Ring rg = {0, 1};
#pragma unroll 1
  for (int r = 0; r < 4; r++) {
    const int seg = 8 * r + 4 * wg + sp;
    if (r < 2) poll_ge(&g_sync[SY_XN + ((8 * (r ? lane & 3 : 0) + 4 * wg + sp) >> 1) * 32], ep * 8);
    __syncwarp();
#pragma unroll 1
    for (int u = 0; u < 9; u++) {
      mbar_wait(c, rb + 8 * B_EMPTY + rg.o, rg.ph);
      if (elect()) {
        const uint32_t fb = rb + 8 * B_FULL + rg.o;
        mbar_expect(fb, 8192);
        bulk_ld(dst + rg.o * 2048, g_xn + ((seg >> 1) * 9 + u) * 1024 + (seg & 1) * 512, 8192, fb);
      }
      ring_next(rg);
    }
  }
  if (!wg) {
#pragma unroll 1
    for (int k = lane >> 1; k < 144; k += 16) pf_l2(P.pw[5 + (lane & 1)] + (512 + 16 * sp) * DM + k * 64);
  } else {
    rg.o = 0; rg.ph = 1;
#pragma unroll 1
    for (int u = 0; u < 21; u++) {
      if (!(u & 15) || u == 20) poll_ge(&g_sync[(u == 20 ? SY_Z : SY_HS) + (4 * (lane & 7) + sp) * 32 + (u >> 4)], u == 16 ? ep : ep * 8);
      __syncwarp();
      if (!u) mbar_wait(c, bar + 8 * B_XN, 0);
      mbar_wait(c, bar + 8 * (B_XN + 1) + rg.o, rg.ph);
      if (elect()) {
        const uint32_t fb = bar + 8 * B_XT + rg.o, st = sb + rg.o * 9216;
        mbar_expect(fb, u < 18 ? 9 * 8192 : 8 * 8192);
        if (u < 18) { tma2d(st + 65536, &P.cre + (u & 1), fb, (u >> 1) * 64, 512); tma2d(st + 69632, &P.cre + (u & 1), fb, (u >> 1) * 64, 544); }
#pragma unroll 1
        for (int k = 0; k < 8; k++) {
          const int seg = 4 * k + sp;
          if (u < 18) tma2d(st + k * 8192, &P.hs, fb, seg * 64, (9 * (u & 1) + (u >> 1)) * 64);
          else if (u == 19) tma_x(st + k * 8192, &P.xp, fb, 512, seg);
          else bulk_ld(st + k * 8192, (u == 18 ? g_xn : g_z) + ((seg >> 1) * 9 + 8) * 1024 + (seg & 1) * 512, 8192, fb);
        }
      }
      rg.o += 8; if (rg.o == 24) { rg.o = 0; rg.ph ^= 1; }
    }
  }
  spin_check(c);
}
DEVI void pf72(const __nv_bfloat16* p, int stride, int lane, int n, int pause) {
  p += (lane >> 1) * stride;
#pragma unroll 1
  for (int k = lane; k < n; k += 24, p += 12 * stride) {
    pf_l2(p);
    asm volatile("nanosleep.u32 %0;" :: "r"(pause));
  }
}
DEVI void main_helper(const Params& P, uint32_t sb, int mi, int j, int lane, uint32_t ep) {
  const uint32_t bar = sb + OFF_BAR;
  uint32_t c = 0;
  mbar_wait(c, bar + 8 * (B_X0 + 2), 0);
  if (lane < 24) pf72(P.pw[lane & 1] + 36 * mi * FF + j * DM, FF, lane, 72, 0);
  else if (lane < 30) asm volatile("prefetch.tensormap [%0];" :: "l"(&P.wd + lane - 24) : "memory");
  __syncwarp();
  mbar_wait(c, bar + 8 * (B_X0 + 5), 0);
  if (lane < 24) pf72(P.pw[3 + (lane & 1)] + (j * 64 + mi * 4) * DM, 64, lane, 72, 0);
  __syncwarp();
  TR(2, 244);
  mbar_wait(c, bar + 8 * B_XN, 0);
  TR(2, 245);
  if (elect()) {
    fence_async_smem();
#pragma unroll 1
    for (int k = 0, n = j == 7 ? 4096 : 2048; k < 8 * n; k += n) { bulk_st(g_xn + (mi * 9 + j) * 1024 + k / 16, sb + k, n); asm volatile("nanosleep.u32 100;"); }
    asm volatile("cp.async.bulk.commit_group;\ncp.async.bulk.wait_group 0;" ::: "memory");
    fence_gpu();
    TR(2, 246);
    red_inc(&g_sync[SY_XN + mi * 32]);
  }
  __syncwarp();
  if (lane < 24) {
#pragma unroll 1
    for (int t = 1; t < 11; t++)
      pf72(t < 9 ? P.pw[lane & 1] + 36 * mi * FF + j * DM + t * 64 : t == 9 ? P.pw[2] + (j * DM + 36 * mi) * DM + (lane & 1) * 64 : P.pw[5 + (lane & 1)] + (j * 64 + mi * 4) * DM,
           t < 9 ? FF : t == 9 ? 128 : 64, lane, t == 9 ? 324 : 72, PFP);
  }
  __syncwarp();
  TR(2, 248);
#pragma unroll 1
  for (int n = 0; n < 18; n++) {
    const int T = n < 8 ? 4 * n + 3 : n + (n < 8 + NC1 ? 25 : 27), U = T & 7;
    const uint32_t fb = bar + 8 * (B_FULLT + U), dst = sb + SLOT + U * UNIT;
    if (n == 0 || n == 4) {
      if (lane < 2) poll_ge(&g_sync[SY_HS + (2 * mi + lane) * 32 + (n >> 2)], n ? ep : ep * 8);
      __syncwarp();
      TR(2, 249);
      mbar_arrive_warp_if(bar + 8 * B_G1, !n);
    }
    mbar_wait(c, n < 2 ? bar + 8 * (B_P2 + n) : bar + 8 * (B_EMPTYT + U), n < 2 ? 0 : ((T >> 3) - 1) & 1);
    if (elect()) {
      mbar_expect(fb, UNIT);
      tma2d_mc(dst + SLOT + (mi & 1) * 4096, &P.cre + (n > 8), fb, (n > 8 ? n - 9 : n) * 64, j * 64 + (mi & 1) * 32);
      asm volatile("cp.async.bulk.tensor.3d.shared::cluster.global.mbarrier::complete_tx::bytes [%0], [%1, {%3, %4, %5}], [%2];"
                   :: "r"(dst), "l"(&P.hs2), "r"(fb), "r"(0), "r"(n * 64), "r"(2 * mi) : "memory");
    }
    TR(2, 100 + T);
  }
  spin_check(c);
}
DEVI void wg_helper(const Params& P, uint32_t sb, int wg, int lane, uint32_t ep) {
  const uint32_t bar = sb + OFF_BAR + 8 * wg;
  const bool mainc = blockIdx.x < 128;
  const int j = CJ(blockIdx.x), mi = CM(blockIdx.x), seg0 = mainc ? 2 * mi + wg : blockIdx.x - 128 + 4 * wg, nr = mainc ? 1 : 4;
  uint32_t c = 0;
  if (mainc) {
    mbar_wait(c, sb + OFF_BAR + 8 * B_XN, 0);
    asm volatile("nanosleep.u32 3000;");
    uint4* zp = g_z + (mi * 9 + j) * 1024 + wg * 512 + lane;
    uint4* z7 = g_z7 + (mi * 8 + j) * 1024 + wg * 512 + lane;
#pragma unroll 1
    for (int k = 0; k < 16; k++) {
      zp[k * 32] = make_uint4(0, 0, 0, 0); z7[k * 32] = make_uint4(~0u, ~0u, ~0u, ~0u);
      if (k < 2) g_z[(mi * 9 + 8) * 1024 + j * 128 + wg * 64 + k * 32 + lane] = make_uint4(0, 0, 0, 0);
      asm volatile("nanosleep.u32 200;");
    }
    __syncwarp();
  }
#pragma unroll 1
  for (int r = 0; r < nr; r++) {
    const int seg = seg0 + 8 * r;
    mbar_wait(c, bar + 8 * B_HS, r & 1);
    TR(2, 223 + 12 * wg);
    if (lane == 0) { fence_async_all(); fence_gpu(); red_inc(&g_sync[SY_HS + seg * 32 + !mainc]); }
    __syncwarp();
    TR(2, 224 + 12 * wg);
  }
  if (mainc) {
    mbar_wait(c, sb + OFF_BAR + 8 * B_G1, 0);
    const uint32_t stg = sb + 13 * SLOT + wg * 8192;
#pragma unroll 1
    for (int b = 0; b < 7; b++) {
      mbar_wait(c, bar + 8 * B_DR, b & 1);
      TR(2, 225 + 12 * wg);
      if (elect()) {
        fence_async_smem();
        bulk_red(g_z + (mi * 9 + blk_of(j, b)) * 1024 + wg * 512, stg, 8192);
        asm volatile("cp.async.bulk.commit_group;\ncp.async.bulk.wait_group.read 0;" ::: "memory");
        mbar_arrive(bar + 8 * B_DF);
        TR(2, 226 + 12 * wg);
        if (b == 0) { mbar_expect(bar + 8 * B_XT, 8192); tma_x(sb + wg * 8192, &P.xp, bar + 8 * B_XT, j * 64, seg0); }
        if (b == 3 || b == 6) {
          asm volatile("cp.async.bulk.wait_group 0;" ::: "memory");
          fence_gpu();
          TR(2, 227 + 12 * wg);
          red_inc(&g_sync[SY_Z + seg0 * 32 + (b == 3)]);
        }
        if (b == 6) {
          mbar_expect(bar + 8 * B_Z, 8192);
          poll_ge(&g_sync[SY_Z + seg0 * 32], ep * 8);
          TR(2, 229 + 12 * wg);
          bulk_ld(stg, g_z + (mi * 9 + j) * 1024 + wg * 512, 8192, bar + 8 * B_Z);
        }
      }
      __syncwarp();
    }
  }
  if (wg == 1 && lane == 0) st_relaxed(&g_sync[SY_EPOCH + blockIdx.x], ep);
  spin_check(c);
}

__global__ void __cluster_dims__(2, 1, 1) __launch_bounds__(384, 1) fused_kernel(const __grid_constant__ Params P) {
  extern __shared__ __align__(1024) uint8_t smem_raw[];
  uint32_t sb = smem_u32(smem_raw);
  asm volatile("" : "+r"(sb));
  const int bid = blockIdx.x, j = CJ(bid), mi = CM(bid);
  const int warp = __shfl_sync(0xffffffffu, threadIdx.x >> 5, 0), lane = threadIdx.x & 31;
  if (warp < 8) {
    TRC(255); TRG(254);
    const int ch = j * 64 + 16 * (warp & 3) + (lane >> 2) + 8 * (lane & 1);
    const __nv_bfloat16 p_re = P.lre[ch], p_im = P.lim[ch], p_dt = P.ldt[ch];
    const uint32_t p_d = *(const uint32_t*)(P.dskip + j * 64 + 2 * lane);
    if (elect()) {
      const uint32_t cnt = (warp & 4) ? (warp == 7 || bid >= 128 ? 4 : 16) : 1;
#pragma unroll
      for (int k = 0; k < 6; k++) mbar_init(sb + OFF_BAR + 48 * warp + 8 * k, k && warp == 6 ? 8 : cnt);
      asm volatile("fence.mbarrier_init.release.cluster;" ::: "memory");
    }
    TR(2, 200 + warp);
    __syncwarp();
    asm volatile("barrier.cluster.arrive.relaxed.aligned;\nbar.sync 0, 384;" ::: "memory");
    TRC(141);
    asm volatile("st.shared.b32 [%0], %1;" :: "r"(sb + OFF_D + (lane & 3) * 32 + (lane & 28)), "r"(p_d) : "memory");
    scan_params(sb + OFF_PAR + (ch & 63) * 16, __bfloat162float(p_re), __bfloat162float(p_im), __bfloat162float(p_dt));
    TRC(142);
    asm volatile("setmaxnreg.inc.sync.aligned.u32 240;");
    TRC(143);
    if (bid >= 128) spare_consumer(P, sb, warp, lane); else main_consumer(P, sb, warp >> 2);
    tr_dump();
  } else {
    if (warp != 8) {
      if (bid < 128 && threadIdx.x < 360) pf_l2(P.x + (mi * 128 + j * 8) * DM + (threadIdx.x - 288) * 64);
    } else {
      if (elect()) {
#pragma unroll
        for (int k = 0; k < 6; k++) mbar_init(sb + OFF_BAR + 8 * (B_X0 + k), 1);
        asm volatile("fence.mbarrier_init.release.cluster;" ::: "memory");
        if (bid < 128) {
          mbar_expect(sb + OFF_BAR + 8 * B_X0, 3 * 8192);
          tma_x(sb, &P.xp, sb + OFF_BAR + 8 * B_X0, j * 64, mi * 2);
#pragma unroll
          for (int k = 1; k < 6; k++) mbar_expect(sb + OFF_BAR + 8 * (B_X0 + k), 3 * 8192);
          asm volatile("prefetch.tensormap [%0];\nprefetch.tensormap [%1];" :: "l"(&P.wg), "l"(&P.wu) : "memory");
        }
      }
      __syncwarp();
    }
    TR(2, 200 + warp);
    asm volatile("barrier.cluster.arrive.relaxed.aligned;\nsetmaxnreg.dec.sync.aligned.u32 24;" ::: "memory");
    if (warp != 8 || bid >= 128) {
      asm volatile("bar.sync 0, 384;" ::: "memory");
      if (PFX && bid < 128) {
        const int t = threadIdx.x - 288;
        if (t < 72) pf_l2(P.x + (mi * 128 + 64 + j * 8) * DM + t * 64);
        else if (t < 80) pf_l2(P.pw[t & 1] + (j * 64 + mi * 4 + ((t >> 1) & 3)) * FF + j * DM);
      }
      const uint32_t ep = ld_epoch();
      if (warp < 10 && bid >= 128) spare_producer(P, sb, bid - 128, warp - 8, lane, ep);
      else if (warp >= 10) wg_helper(P, sb, warp - 10, lane, ep);
      else main_helper(P, sb, mi, j, lane, ep);
    } else {
      asm volatile("bar.arrive 0, 384;" ::: "memory");
      main_producer(P, sb, mi, j);
    }
  }
}
typedef CUresult (*EncodeFn)(CUtensorMap*, CUtensorMapDataType, cuuint32_t, void*, const cuuint64_t*, const cuuint64_t*, const cuuint32_t*,
                             const cuuint32_t*, CUtensorMapInterleave, CUtensorMapSwizzle, CUtensorMapL2promotion, CUtensorMapFloatOOBfill);
static void make_map(EncodeFn enc, CUtensorMap* m, const void* ptr, int rank, const cuuint64_t* dims, const cuuint64_t* strides, const cuuint32_t* box) {
  const cuuint32_t es[5] = {1, 1, 1, 1, 1};
  enc(m, CU_TENSOR_MAP_DATA_TYPE_BFLOAT16, rank, (void*)ptr, dims, strides, box, es, CU_TENSOR_MAP_INTERLEAVE_NONE,
      CU_TENSOR_MAP_SWIZZLE_128B, CU_TENSOR_MAP_L2_PROMOTION_L2_128B, CU_TENSOR_MAP_FLOAT_OOB_FILL_NONE);
}
static void map2d(EncodeFn enc, CUtensorMap* m, const void* ptr, uint64_t inner, uint64_t outer, cuuint32_t rows = 64) {
  const cuuint64_t dims[2] = {inner, outer}, strides[1] = {inner * 2};
  const cuuint32_t box[2] = {64, rows};
  make_map(enc, m, ptr, 2, dims, strides, box);
}

extern "C" void kernel_launch(void* const* d_in, const int* in_sizes, int n_in, void* d_out, int out_size) {
  void* fn = nullptr;
  cudaDriverEntryPointQueryResult st;
  cudaGetDriverEntryPoint("cuTensorMapEncodeTiled", &fn, cudaEnableDefault, &st);
  EncodeFn enc = (EncodeFn)fn;
  void* hs = nullptr;
  cudaGetSymbolAddress(&hs, g_hsT);
  Params P;
  map2d(enc, &P.wg, d_in[10], FF, DM); map2d(enc, &P.wu, d_in[11], FF, DM); map2d(enc, &P.wd, d_in[12], DM, FF, 96);
  map2d(enc, &P.bre, d_in[3], DM, DM); map2d(enc, &P.bim, d_in[4], DM, DM);
  map2d(enc, &P.cre, d_in[5], DM, DM, 32); map2d(enc, &P.cim, d_in[6], DM, DM, 32);
  map2d(enc, &P.hs, hs, SEQ, 2 * DM);
  {
    const cuuint64_t dims[3] = {64, 2 * DM, SEQ / 64}, strides[2] = {SEQ * 2, 128};
    const cuuint32_t box[3] = {64, 64, 2};
    make_map(enc, &P.hs2, hs, 3, dims, strides, box);
  }
  {
    const cuuint64_t dims[5] = {DM, 2, 4, 8, 32}, strides[4] = {DM * 2, 16 * DM * 2, 2 * DM * 2, 64 * DM * 2};
    const cuuint32_t box[5] = {64, 2, 4, 8, 1};
    make_map(enc, &P.xp, d_in[0], 5, dims, strides, box);
  }
  P.x = (const __nv_bfloat16*)d_in[0]; P.lre = (const __nv_bfloat16*)d_in[1]; P.lim = (const __nv_bfloat16*)d_in[2];
  P.ldt = (const __nv_bfloat16*)d_in[7]; P.dskip = (const __nv_bfloat16*)d_in[8];
  const int pi[7] = {10, 11, 12, 3, 4, 5, 6};
  for (int i = 0; i < 7; i++) P.pw[i] = (const __nv_bfloat16*)d_in[pi[i]];
  P.out = (float*)d_out;
  P.desc = DESC0;
  cudaFuncSetAttribute(fused_kernel, cudaFuncAttributeMaxDynamicSharedMemorySize, SMEM_BYTES);
  fused_kernel<<<132, 384, SMEM_BYTES, cudaStreamPerThread>>>(P);
}
```

```cpp
#include <cuda_runtime.h>
#include <cuda.h>
#include <cuda_bf16.h>
#include <stdint.h>

#define DEVI __device__ __forceinline__
template<int TA,int TB,uint32_t OA,uint32_t OB> DEVI void wg_ss64(float (&d)[32], uint64_t da, uint64_t db) {
  asm volatile("{\n.reg .pred p;\n.reg .b64 x,y;\nsetp.eq.b32 p,1,1;\nadd.s64 x,%32,%36;\nadd.s64 y,%33,%37;\n"
    "wgmma.mma_async.sync.aligned.m64n64k16.f32.bf16.bf16 "
    "{%0,%1,%2,%3,%4,%5,%6,%7,%8,%9,%10,%11,%12,%13,%14,%15,%16,%17,%18,%19,%20,%21,%22,%23,%24,%25,%26,%27,%28,%29,%30,%31},x,y,p,1,1,%34,%35;\n}\n"
    : "+f"(d[0]),"+f"(d[1]),"+f"(d[2]),"+f"(d[3]),"+f"(d[4]),"+f"(d[5]),"+f"(d[6]),"+f"(d[7]),"+f"(d[8]),"+f"(d[9]),"+f"(d[10]),"+f"(d[11]),"+f"(d[12]),"+f"(d[13]),"+f"(d[14]),"+f"(d[15]),"+f"(d[16]),"+f"(d[17]),"+f"(d[18]),"+f"(d[19]),"+f"(d[20]),"+f"(d[21]),"+f"(d[22]),"+f"(d[23]),"+f"(d[24]),"+f"(d[25]),"+f"(d[26]),"+f"(d[27]),"+f"(d[28]),"+f"(d[29]),"+f"(d[30]),"+f"(d[31])
    : "l"(da),"l"(db),"n"(TA),"n"(TB),"n"(OA),"n"(OB));
}
template<int TA,int TB,uint32_t OA,uint32_t OB> DEVI void wg_ss64p(float (&d)[32], uint64_t da, uint64_t db, int f) {
  asm volatile("{\n.reg .pred p;\n.reg .b64 x,y;\nsetp.ne.b32 p,%38,0;\nadd.s64 x,%32,%36;\nadd.s64 y,%33,%37;\n"
    "wgmma.mma_async.sync.aligned.m64n64k16.f32.bf16.bf16 "
    "{%0,%1,%2,%3,%4,%5,%6,%7,%8,%9,%10,%11,%12,%13,%14,%15,%16,%17,%18,%19,%20,%21,%22,%23,%24,%25,%26,%27,%28,%29,%30,%31},x,y,p,1,1,%34,%35;\n}\n"
    : "+f"(d[0]),"+f"(d[1]),"+f"(d[2]),"+f"(d[3]),"+f"(d[4]),"+f"(d[5]),"+f"(d[6]),"+f"(d[7]),"+f"(d[8]),"+f"(d[9]),"+f"(d[10]),"+f"(d[11]),"+f"(d[12]),"+f"(d[13]),"+f"(d[14]),"+f"(d[15]),"+f"(d[16]),"+f"(d[17]),"+f"(d[18]),"+f"(d[19]),"+f"(d[20]),"+f"(d[21]),"+f"(d[22]),"+f"(d[23]),"+f"(d[24]),"+f"(d[25]),"+f"(d[26]),"+f"(d[27]),"+f"(d[28]),"+f"(d[29]),"+f"(d[30]),"+f"(d[31])
    : "l"(da),"l"(db),"n"(TA),"n"(TB),"n"(OA),"n"(OB),"r"(f));
}
template<int TA,int TB,uint32_t OA,uint32_t OB> DEVI void wg_ss128(float (&d)[64], uint64_t da, uint64_t db) {
  asm volatile("{\n.reg .pred p;\n.reg .b64 x,y;\nsetp.eq.b32 p,1,1;\nadd.s64 x,%64,%68;\nadd.s64 y,%65,%69;\n"
    "wgmma.mma_async.sync.aligned.m64n128k16.f32.bf16.bf16 "
    "{%0,%1,%2,%3,%4,%5,%6,%7,%8,%9,%10,%11,%12,%13,%14,%15,%16,%17,%18,%19,%20,%21,%22,%23,%24,%25,%26,%27,%28,%29,%30,%31,%32,%33,%34,%35,%36,%37,%38,%39,%40,%41,%42,%43,%44,%45,%46,%47,%48,%49,%50,%51,%52,%53,%54,%55,%56,%57,%58,%59,%60,%61,%62,%63},x,y,p,1,1,%66,%67;\n}\n"
    : "+f"(d[0]),"+f"(d[1]),"+f"(d[2]),"+f"(d[3]),"+f"(d[4]),"+f"(d[5]),"+f"(d[6]),"+f"(d[7]),"+f"(d[8]),"+f"(d[9]),"+f"(d[10]),"+f"(d[11]),"+f"(d[12]),"+f"(d[13]),"+f"(d[14]),"+f"(d[15]),"+f"(d[16]),"+f"(d[17]),"+f"(d[18]),"+f"(d[19]),"+f"(d[20]),"+f"(d[21]),"+f"(d[22]),"+f"(d[23]),"+f"(d[24]),"+f"(d[25]),"+f"(d[26]),"+f"(d[27]),"+f"(d[28]),"+f"(d[29]),"+f"(d[30]),"+f"(d[31]),"+f"(d[32]),"+f"(d[33]),"+f"(d[34]),"+f"(d[35]),"+f"(d[36]),"+f"(d[37]),"+f"(d[38]),"+f"(d[39]),"+f"(d[40]),"+f"(d[41]),"+f"(d[42]),"+f"(d[43]),"+f"(d[44]),"+f"(d[45]),"+f"(d[46]),"+f"(d[47]),"+f"(d[48]),"+f"(d[49]),"+f"(d[50]),"+f"(d[51]),"+f"(d[52]),"+f"(d[53]),"+f"(d[54]),"+f"(d[55]),"+f"(d[56]),"+f"(d[57]),"+f"(d[58]),"+f"(d[59]),"+f"(d[60]),"+f"(d[61]),"+f"(d[62]),"+f"(d[63])
    : "l"(da),"l"(db),"n"(TA),"n"(TB),"n"(OA),"n"(OB));
}
template<int TA,int TB,uint32_t OA,uint32_t OB> DEVI void wg_ss128p(float (&d)[64], uint64_t da, uint64_t db, int f) {
  asm volatile("{\n.reg .pred p;\n.reg .b64 x,y;\nsetp.ne.b32 p,%70,0;\nadd.s64 x,%64,%68;\nadd.s64 y,%65,%69;\n"
    "wgmma.mma_async.sync.aligned.m64n128k16.f32.bf16.bf16 "
    "{%0,%1,%2,%3,%4,%5,%6,%7,%8,%9,%10,%11,%12,%13,%14,%15,%16,%17,%18,%19,%20,%21,%22,%23,%24,%25,%26,%27,%28,%29,%30,%31,%32,%33,%34,%35,%36,%37,%38,%39,%40,%41,%42,%43,%44,%45,%46,%47,%48,%49,%50,%51,%52,%53,%54,%55,%56,%57,%58,%59,%60,%61,%62,%63},x,y,p,1,1,%66,%67;\n}\n"
    : "+f"(d[0]),"+f"(d[1]),"+f"(d[2]),"+f"(d[3]),"+f"(d[4]),"+f"(d[5]),"+f"(d[6]),"+f"(d[7]),"+f"(d[8]),"+f"(d[9]),"+f"(d[10]),"+f"(d[11]),"+f"(d[12]),"+f"(d[13]),"+f"(d[14]),"+f"(d[15]),"+f"(d[16]),"+f"(d[17]),"+f"(d[18]),"+f"(d[19]),"+f"(d[20]),"+f"(d[21]),"+f"(d[22]),"+f"(d[23]),"+f"(d[24]),"+f"(d[25]),"+f"(d[26]),"+f"(d[27]),"+f"(d[28]),"+f"(d[29]),"+f"(d[30]),"+f"(d[31]),"+f"(d[32]),"+f"(d[33]),"+f"(d[34]),"+f"(d[35]),"+f"(d[36]),"+f"(d[37]),"+f"(d[38]),"+f"(d[39]),"+f"(d[40]),"+f"(d[41]),"+f"(d[42]),"+f"(d[43]),"+f"(d[44]),"+f"(d[45]),"+f"(d[46]),"+f"(d[47]),"+f"(d[48]),"+f"(d[49]),"+f"(d[50]),"+f"(d[51]),"+f"(d[52]),"+f"(d[53]),"+f"(d[54]),"+f"(d[55]),"+f"(d[56]),"+f"(d[57]),"+f"(d[58]),"+f"(d[59]),"+f"(d[60]),"+f"(d[61]),"+f"(d[62]),"+f"(d[63])
    : "l"(da),"l"(db),"n"(TA),"n"(TB),"n"(OA),"n"(OB),"r"(f));
}
template<int TB,uint32_t OB> DEVI void wg_rs64(float (&d)[32], const uint32_t* a, uint64_t db) {
  asm volatile("{\n.reg .pred p;\n.reg .b64 y;\nsetp.eq.b32 p,1,1;\nadd.s64 y,%36,%38;\n"
    "wgmma.mma_async.sync.aligned.m64n64k16.f32.bf16.bf16 "
    "{%0,%1,%2,%3,%4,%5,%6,%7,%8,%9,%10,%11,%12,%13,%14,%15,%16,%17,%18,%19,%20,%21,%22,%23,%24,%25,%26,%27,%28,%29,%30,%31},{%32,%33,%34,%35},y,p,1,1,%37;\n}\n"
    : "+f"(d[0]),"+f"(d[1]),"+f"(d[2]),"+f"(d[3]),"+f"(d[4]),"+f"(d[5]),"+f"(d[6]),"+f"(d[7]),"+f"(d[8]),"+f"(d[9]),"+f"(d[10]),"+f"(d[11]),"+f"(d[12]),"+f"(d[13]),"+f"(d[14]),"+f"(d[15]),"+f"(d[16]),"+f"(d[17]),"+f"(d[18]),"+f"(d[19]),"+f"(d[20]),"+f"(d[21]),"+f"(d[22]),"+f"(d[23]),"+f"(d[24]),"+f"(d[25]),"+f"(d[26]),"+f"(d[27]),"+f"(d[28]),"+f"(d[29]),"+f"(d[30]),"+f"(d[31])
    : "r"(a[0]),"r"(a[1]),"r"(a[2]),"r"(a[3]),"l"(db),"n"(TB),"n"(OB));
}
template<int TB,uint32_t OB> DEVI void wg_rs64z(float (&d)[32], const uint32_t* a, uint64_t db) {
  asm volatile("{\n.reg .pred p;\n.reg .b64 y;\nsetp.ne.b32 p,1,1;\nadd.s64 y,%36,%38;\n"
    "wgmma.mma_async.sync.aligned.m64n64k16.f32.bf16.bf16 "
    "{%0,%1,%2,%3,%4,%5,%6,%7,%8,%9,%10,%11,%12,%13,%14,%15,%16,%17,%18,%19,%20,%21,%22,%23,%24,%25,%26,%27,%28,%29,%30,%31},{%32,%33,%34,%35},y,p,1,1,%37;\n}\n"
    : "=f"(d[0]),"=f"(d[1]),"=f"(d[2]),"=f"(d[3]),"=f"(d[4]),"=f"(d[5]),"=f"(d[6]),"=f"(d[7]),"=f"(d[8]),"=f"(d[9]),"=f"(d[10]),"=f"(d[11]),"=f"(d[12]),"=f"(d[13]),"=f"(d[14]),"=f"(d[15]),"=f"(d[16]),"=f"(d[17]),"=f"(d[18]),"=f"(d[19]),"=f"(d[20]),"=f"(d[21]),"=f"(d[22]),"=f"(d[23]),"=f"(d[24]),"=f"(d[25]),"=f"(d[26]),"=f"(d[27]),"=f"(d[28]),"=f"(d[29]),"=f"(d[30]),"=f"(d[31])
    : "r"(a[0]),"r"(a[1]),"r"(a[2]),"r"(a[3]),"l"(db),"n"(TB),"n"(OB));
}
template<int TB,uint32_t OB> DEVI void wg_rs128(float (&d)[64], const uint32_t* a, uint64_t db) {
  asm volatile("{\n.reg .pred p;\n.reg .b64 y;\nsetp.eq.b32 p,1,1;\nadd.s64 y,%68,%70;\n"
    "wgmma.mma_async.sync.aligned.m64n128k16.f32.bf16.bf16 "
    "{%0,%1,%2,%3,%4,%5,%6,%7,%8,%9,%10,%11,%12,%13,%14,%15,%16,%17,%18,%19,%20,%21,%22,%23,%24,%25,%26,%27,%28,%29,%30,%31,%32,%33,%34,%35,%36,%37,%38,%39,%40,%41,%42,%43,%44,%45,%46,%47,%48,%49,%50,%51,%52,%53,%54,%55,%56,%57,%58,%59,%60,%61,%62,%63},{%64,%65,%66,%67},y,p,1,1,%69;\n}\n"
    : "+f"(d[0]),"+f"(d[1]),"+f"(d[2]),"+f"(d[3]),"+f"(d[4]),"+f"(d[5]),"+f"(d[6]),"+f"(d[7]),"+f"(d[8]),"+f"(d[9]),"+f"(d[10]),"+f"(d[11]),"+f"(d[12]),"+f"(d[13]),"+f"(d[14]),"+f"(d[15]),"+f"(d[16]),"+f"(d[17]),"+f"(d[18]),"+f"(d[19]),"+f"(d[20]),"+f"(d[21]),"+f"(d[22]),"+f"(d[23]),"+f"(d[24]),"+f"(d[25]),"+f"(d[26]),"+f"(d[27]),"+f"(d[28]),"+f"(d[29]),"+f"(d[30]),"+f"(d[31]),"+f"(d[32]),"+f"(d[33]),"+f"(d[34]),"+f"(d[35]),"+f"(d[36]),"+f"(d[37]),"+f"(d[38]),"+f"(d[39]),"+f"(d[40]),"+f"(d[41]),"+f"(d[42]),"+f"(d[43]),"+f"(d[44]),"+f"(d[45]),"+f"(d[46]),"+f"(d[47]),"+f"(d[48]),"+f"(d[49]),"+f"(d[50]),"+f"(d[51]),"+f"(d[52]),"+f"(d[53]),"+f"(d[54]),"+f"(d[55]),"+f"(d[56]),"+f"(d[57]),"+f"(d[58]),"+f"(d[59]),"+f"(d[60]),"+f"(d[61]),"+f"(d[62]),"+f"(d[63])
    : "r"(a[0]),"r"(a[1]),"r"(a[2]),"r"(a[3]),"l"(db),"n"(TB),"n"(OB));
}
template<int TB,uint32_t OB> DEVI void wg_rs128z(float (&d)[64], const uint32_t* a, uint64_t db) {
  asm volatile("{\n.reg .pred p;\n.reg .b64 y;\nsetp.ne.b32 p,1,1;\nadd.s64 y,%68,%70;\n"
    "wgmma.mma_async.sync.aligned.m64n128k16.f32.bf16.bf16 "
    "{%0,%1,%2,%3,%4,%5,%6,%7,%8,%9,%10,%11,%12,%13,%14,%15,%16,%17,%18,%19,%20,%21,%22,%23,%24,%25,%26,%27,%28,%29,%30,%31,%32,%33,%34,%35,%36,%37,%38,%39,%40,%41,%42,%43,%44,%45,%46,%47,%48,%49,%50,%51,%52,%53,%54,%55,%56,%57,%58,%59,%60,%61,%62,%63},{%64,%65,%66,%67},y,p,1,1,%69;\n}\n"
    : "=f"(d[0]),"=f"(d[1]),"=f"(d[2]),"=f"(d[3]),"=f"(d[4]),"=f"(d[5]),"=f"(d[6]),"=f"(d[7]),"=f"(d[8]),"=f"(d[9]),"=f"(d[10]),"=f"(d[11]),"=f"(d[12]),"=f"(d[13]),"=f"(d[14]),"=f"(d[15]),"=f"(d[16]),"=f"(d[17]),"=f"(d[18]),"=f"(d[19]),"=f"(d[20]),"=f"(d[21]),"=f"(d[22]),"=f"(d[23]),"=f"(d[24]),"=f"(d[25]),"=f"(d[26]),"=f"(d[27]),"=f"(d[28]),"=f"(d[29]),"=f"(d[30]),"=f"(d[31]),"=f"(d[32]),"=f"(d[33]),"=f"(d[34]),"=f"(d[35]),"=f"(d[36]),"=f"(d[37]),"=f"(d[38]),"=f"(d[39]),"=f"(d[40]),"=f"(d[41]),"=f"(d[42]),"=f"(d[43]),"=f"(d[44]),"=f"(d[45]),"=f"(d[46]),"=f"(d[47]),"=f"(d[48]),"=f"(d[49]),"=f"(d[50]),"=f"(d[51]),"=f"(d[52]),"=f"(d[53]),"=f"(d[54]),"=f"(d[55]),"=f"(d[56]),"=f"(d[57]),"=f"(d[58]),"=f"(d[59]),"=f"(d[60]),"=f"(d[61]),"=f"(d[62]),"=f"(d[63])
    : "r"(a[0]),"r"(a[1]),"r"(a[2]),"r"(a[3]),"l"(db),"n"(TB),"n"(OB));
}

constexpr int SEQ = 2048, DM = 576, FF = 4608;
constexpr uint32_t SLOT = 16384;
constexpr uint32_t OFF_BAR = 14 * SLOT;
constexpr uint32_t OFF_PAR = OFF_BAR + 512;
constexpr uint32_t OFF_D = OFF_PAR + 1024;
constexpr uint32_t SMEM_BYTES = OFF_D + 256;
constexpr int B_X0 = 48, B_P2 = 0, B_FULL = 2, B_FULLT = 7, B_XT = 15, B_DF = 17, B_Z = 19, B_RES = 21, B_G1 = 23,
              B_EMPTY = 24, B_EMPTYT = 29, B_XN = 37, B_HS = 44, B_DR = 46;
#define VP 2
DEVI int vpair(int k) {
  const int t = k - 4, d = ((k - 36) * 37) >> 8;
  return k < 4 ? k : k < 36 ? (t & 7) * 8 + (t >> 3) + (t & 7 ? 0 : 4) : (k - 35 - 7 * d) * 8 + 4 + d;
}
#define CJ(b) ((int)(b) >= 128 ? 8 : vpair((int)(b) >> 1) & 7)
#define CM(b) ((vpair((int)(b) >> 1) >> 3) * 2 + ((int)(b) & 1))
constexpr uint32_t SPIN_MAX = 400000;

struct alignas(64) Params {
  CUtensorMap wg, wu, wd, bre, bim, cre, cim, hs2, hs, xp;
  const __nv_bfloat16 *x, *lre, *lim, *ldt, *dskip, *pw[7];
  float* out;
  uint64_t desc;
};

__device__ __align__(1024) uint4 g_hsT[1152 * SEQ / 8];
__device__ __align__(1024) uint4 g_xn[16 * 9 * 1024];
__device__ __align__(1024) uint4 g_z[16 * 9 * 1024];
__device__ __align__(1024) uint4 g_z7[16 * 8 * 1024];
__device__ __align__(1024) float4 g_state[9 * 32 * 32];
constexpr int SY_EPOCH = 0, SY_XN = 160, SY_HS = SY_XN + 16 * 32, SY_Z = SY_HS + 32 * 32;
__device__ __align__(1024) uint32_t g_sync[SY_Z + 32 * 32];
#define TR(role, idx)
#define TRC(idx)
#define TRG(idx)
DEVI void tr_dump() {}

DEVI uint32_t smem_u32(const void* p) { return (uint32_t)__cvta_generic_to_shared(p); }
DEVI void mbar_init(uint32_t bar, uint32_t cnt) { asm volatile("mbarrier.init.shared::cta.b64 [%0], %1;" :: "r"(bar), "r"(cnt)); }
DEVI void mbar_expect(uint32_t bar, uint32_t bytes) { asm volatile("mbarrier.arrive.expect_tx.shared::cta.b64 _, [%0], %1;" :: "r"(bar), "r"(bytes) : "memory"); }
DEVI void mbar_arrive(uint32_t bar) { asm volatile("mbarrier.arrive.shared::cta.b64 _, [%0];" :: "r"(bar) : "memory"); }
DEVI void mbar_arrive_warp(uint32_t bar) {
  asm volatile("{\n.reg .pred p;\nelect.sync _|p, 0xffffffff;\n@p mbarrier.arrive.shared::cta.b64 _, [%0];\n}" :: "r"(bar) : "memory");
}
DEVI void mbar_arrive_warp_if(uint32_t bar, int f) {
  asm volatile("{\n.reg .pred p, q;\nelect.sync _|p, 0xffffffff;\nsetp.ne.and.b32 q, %1, 0, p;\n@q mbarrier.arrive.shared::cta.b64 _, [%0];\n}" :: "r"(bar), "r"(f) : "memory");
}
DEVI void mbar_arrive2(uint32_t bar, uint32_t rbar, uint32_t o, int f = 1) {
  asm volatile("{\n.reg .pred p, q;\nelect.sync _|p, 0xffffffff;\nsetp.ne.and.b32 q, %2, 0, p;\n@q mbarrier.arrive.shared::cta.b64 _, [%0];\n"
               "@q mbarrier.arrive.shared::cluster.b64 _, [%1];\n}" :: "r"(bar + o), "r"(rbar + o), "r"(f) : "memory");
}
DEVI void mbar_wait(uint32_t& c, uint32_t bar, uint32_t parity) {
  asm volatile("{\n.reg .pred p, q;\nLW:\nadd.u32 %0, %0, 1;\nsetp.lt.u32 q, %0, %3;\n"
               "mbarrier.try_wait.parity.shared::cta.b64 p, [%1], %2;\nnot.pred p, p;\nand.pred p, p, q;\n@p bra LW;\n}"
               : "+&r"(c) : "r"(bar), "r"(parity), "n"(SPIN_MAX) : "memory");
}
DEVI void spin_check(uint32_t c) { asm volatile("{\n.reg .pred p;\nsetp.ge.u32 p, %0, %1;\n@p trap;\n}" :: "r"(c), "n"(SPIN_MAX)); }
DEVI bool elect() { uint32_t p; asm volatile("{\n.reg .pred p;\nelect.sync _|p, 0xffffffff;\nselp.u32 %0, 1, 0, p;\n}" : "=r"(p)); return p; }
DEVI void poll_ge(const uint32_t* p, uint32_t target) {
  asm volatile("{\n.reg .pred p;\n.reg .u32 c, v;\nmov.u32 c, 0;\nLW:\n"
               "ld.relaxed.gpu.global.u32 v, [%0];\nsub.u32 v, v, %1;\nsetp.ge.s32 p, v, 0;\n@p bra LD;\n"
               "nanosleep.u32 40;\nadd.u32 c, c, 1;\nsetp.gt.u32 p, c, 2000000;\n@p trap;\nbra LW;\nLD:\n}" :: "l"(p), "r"(target) : "memory");
}
DEVI void fence_gpu() { asm volatile("fence.acq_rel.gpu;" ::: "memory"); }
DEVI void fence_async_all() { asm volatile("fence.proxy.async;" ::: "memory"); }
DEVI void fence_async_smem() { asm volatile("fence.proxy.async.shared::cta;" ::: "memory"); }
DEVI void red_inc(uint32_t* p) { asm volatile("red.relaxed.gpu.global.add.u32 [%0], 1;" :: "l"(p) : "memory"); }
DEVI void st_relaxed(uint32_t* p, uint32_t v) { asm volatile("st.relaxed.gpu.global.u32 [%0], %1;" :: "l"(p), "r"(v) : "memory"); }
DEVI uint32_t ld_relaxed(const uint32_t* p) { uint32_t v; asm volatile("ld.relaxed.gpu.global.u32 %0, [%1];" : "=r"(v) : "l"(p) : "memory"); return v; }
DEVI void tma2d(uint32_t dst, const CUtensorMap* m, uint32_t bar, int c0, int c1) {
  asm volatile("cp.async.bulk.tensor.2d.shared::cluster.global.mbarrier::complete_tx::bytes [%0], [%1, {%3, %4}], [%2];"
               :: "r"(dst), "l"(m), "r"(bar), "r"(c0), "r"(c1) : "memory");
}
DEVI void tma2d_mc(uint32_t dst, const CUtensorMap* m, uint32_t bar, int c0, int c1) {
  asm volatile("cp.async.bulk.tensor.2d.shared::cluster.global.mbarrier::complete_tx::bytes.multicast::cluster [%0], [%1, {%3, %4}], [%2], %5;"
               :: "r"(dst), "l"(m), "r"(bar), "r"(c0), "r"(c1), "h"((uint16_t)3) : "memory");
}
DEVI void tma_x(uint32_t dst, const CUtensorMap* m, uint32_t bar, int col, int seg) {
  asm volatile("cp.async.bulk.tensor.5d.shared::cluster.global.mbarrier::complete_tx::bytes [%0], [%1, {%3, %5, %5, %5, %4}], [%2];"
               :: "r"(dst), "l"(m), "r"(bar), "r"(col), "r"(seg), "r"(0) : "memory");
}
DEVI void pf_l2(const void* p) { asm volatile("prefetch.global.L2 [%0];" :: "l"(p) : "memory"); }
DEVI void bulk_ld(uint32_t dst, const void* src, uint32_t bytes, uint32_t bar) {
  asm volatile("cp.async.bulk.shared::cluster.global.mbarrier::complete_tx::bytes [%0], [%1], %2, [%3];" :: "r"(dst), "l"(src), "r"(bytes), "r"(bar) : "memory");
}
DEVI void bulk_st(void* dst, uint32_t src, uint32_t bytes) {
  asm volatile("cp.async.bulk.global.shared::cta.bulk_group [%0], [%1], %2;" :: "l"(dst), "r"(src), "r"(bytes) : "memory");
}
DEVI void bulk_red(void* dst, uint32_t src, uint32_t bytes) {
  asm volatile("cp.reduce.async.bulk.global.shared::cta.bulk_group.add.noftz.bf16 [%0], [%1], %2;" :: "l"(dst), "r"(src), "r"(bytes) : "memory");
}
DEVI void wg_fence() { asm volatile("wgmma.fence.sync.aligned;" ::: "memory"); }
#define HINT 0
DEVI void mbar_wait_h(uint32_t& c, uint32_t bar, uint32_t parity) {
  mbar_wait(c, bar, parity);
}
DEVI void mbar_wait_f(uint32_t& c, uint32_t bar, uint32_t parity) { mbar_wait(c, bar, parity); wg_fence(); }
DEVI void wg_commit() { asm volatile("wgmma.commit_group.sync.aligned;" ::: "memory"); }
template <int N> DEVI void wg_wait() { asm volatile("wgmma.wait_group.sync.aligned %0;" :: "n"(N) : "memory"); }
template <int N> DEVI void pin(float (&a)[N]) {
#pragma unroll
  for (int i = 0; i < N; i++) asm volatile("" : "+f"(a[i]) :: "memory");
}
template <int N> DEVI void pinu(uint32_t (&a)[N]) {
#pragma unroll
  for (int i = 0; i < N; i++) asm volatile("" : "+r"(a[i]) :: "memory");
}
constexpr uint64_t DESC0 = (512ull << 16) | (0x40000040ull << 32);
DEVI uint32_t pack2(float lo, float hi) { uint32_t r; asm("cvt.rn.bf16x2.f32 %0, %1, %2;" : "=r"(r) : "f"(hi), "f"(lo)); return r; }
DEVI uint32_t hmul2(uint32_t a, uint32_t b) { uint32_t r; asm("mul.rn.bf16x2 %0, %1, %2;" : "=r"(r) : "r"(a), "r"(b)); return r; }
DEVI uint32_t hadd2(uint32_t a, uint32_t b) { uint32_t r; asm("add.rn.bf16x2 %0, %1, %2;" : "=r"(r) : "r"(a), "r"(b)); return r; }
DEVI uint32_t hfma2(uint32_t a, uint32_t b, uint32_t c) { uint32_t r; asm("fma.rn.bf16x2 %0, %1, %2, %3;" : "=r"(r) : "r"(a), "r"(b), "r"(c)); return r; }
DEVI float blo(uint32_t v) { return __uint_as_float(v << 16); }
DEVI float bhi(uint32_t v) { return __uint_as_float(v & 0xffff0000u); }
DEVI float bround(float f) { return __bfloat162float(__float2bfloat16_rn(f)); }
DEVI void mma16816(float (&d)[4], uint32_t a0, uint32_t a1, uint32_t a2, uint32_t a3, uint32_t b0, uint32_t b1) {
  asm volatile("mma.sync.aligned.m16n8k16.row.col.f32.bf16.bf16.f32 {%0,%1,%2,%3}, {%4,%5,%6,%7}, {%8,%9}, {%0,%1,%2,%3};"
               : "+f"(d[0]), "+f"(d[1]), "+f"(d[2]), "+f"(d[3]) : "r"(a0), "r"(a1), "r"(a2), "r"(a3), "r"(b0), "r"(b1));
}
DEVI void ldsm4(uint32_t* r, uint32_t addr) {
  asm volatile("ldmatrix.sync.aligned.m8n8.x4.shared.b16 {%0,%1,%2,%3}, [%4];" : "=r"(r[0]), "=r"(r[1]), "=r"(r[2]), "=r"(r[3]) : "r"(addr) : "memory");
}
DEVI void stsm4(uint32_t addr, const uint32_t* r) {
  asm volatile("stmatrix.sync.aligned.m8n8.x4.shared.b16 [%4], {%0,%1,%2,%3};" :: "r"(r[0]), "r"(r[1]), "r"(r[2]), "r"(r[3]), "r"(addr) : "memory");
}
template <int I> struct IC { static constexpr int v = I; };
template <int I, int N, class Fn> DEVI void sfor(Fn&& f) { if constexpr (I < N) { f(IC<I>{}); sfor<I + 1, N>(f); } }

struct Scan {
  float lr[2], li[2];
  float cr[2], ci[2];
  float pr[2], pi[2];
  float hr[2], hi[2];
};
constexpr int W_Q = 0, W_F = 4, W_G = 8, W_L = 16;
DEVI float uf(uint32_t v) { return __uint_as_float(v); }
DEVI uint32_t fu(float v) { return __float_as_uint(v); }
DEVI void csq(float& r, float& i) { float t = r * i; r = fmaf(r, r, -i * i); i = t + t; }
DEVI void cmul(float& r, float& i, float ar, float ai) { float t = fmaf(r, ar, -i * ai); i = fmaf(r, ai, i * ar); r = t; }

DEVI void scan_params(uint32_t dst, float a, float b, float ldt) {
  const float dt = bround(expf(ldt));
  const float e = expf(dt * a);
  float sn, cs; sincosf(dt * b, &sn, &cs);
  const float lr = e * cs, li = e * sn, nr = lr - 1.0f;
  const bool sw = fabsf(a) >= fabsf(b);
  const float big = sw ? a : b, sml = sw ? b : a, t = sml / big, d = 2.0f / fmaf(sml, t, big);
  const float cr = (sw ? fmaf(li, t, nr) : fmaf(nr, t, li)) * d, ci = (sw ? fmaf(-nr, t, li) : fmaf(li, t, -nr)) * d;
  asm volatile("st.shared.v4.f32 [%0], {%1,%2,%3,%4};" :: "r"(dst), "f"(lr), "f"(li), "f"(cr), "f"(ci) : "memory");
  __syncwarp();
}
DEVI void scan_load(Scan& s, uint32_t src) {
#pragma unroll
  for (int c = 0; c < 2; c++)
    asm volatile("ld.shared.v4.f32 {%0,%1,%2,%3}, [%4];" : "=f"(s.lr[c]), "=f"(s.li[c]), "=f"(s.cr[c]), "=f"(s.ci[c]) : "r"(src + 128 * c) : "memory");
}
DEVI uint64_t fresh(uint64_t d, uint32_t c) { return d + (c >> 24); }
DEVI uint32_t ld_epoch() { uint32_t l; asm volatile("mov.u32 %0, %%laneid;" : "=r"(l)); return ld_relaxed(&g_sync[SY_EPOCH + blockIdx.x + (l >> 5)]) + 1; }
DEVI uint32_t tid_x() { uint32_t v; asm volatile("mov.u32 %0, %%tid.x;" : "=r"(v)); return v; }
template <int T0, int T1> DEVI void scan_p1(Scan& s, const float (&ur)[32], const float (&ui)[32]) {
#pragma unroll
  for (int t = T0; t < T1; t++)
#pragma unroll
    for (int c = 0; c < 2; c++) {
      const int a = 4 * (t >> 1) + 2 * c + (t & 1);
      if (t == 0) { s.hr[c] = ur[a]; s.hi[c] = ui[a]; }
      else {
        const float tr = fmaf(s.lr[c], s.hr[c], ur[a]), ti = fmaf(s.lr[c], s.hi[c], ui[a]);
        const float nr = fmaf(-s.li[c], s.hi[c], tr); s.hi[c] = fmaf(s.li[c], s.hr[c], ti); s.hr[c] = nr;
      }
    }
}
DEVI void scan_pow16(Scan& s) {
  pin(s.lr); pin(s.li);
#pragma unroll
  for (int c = 0; c < 2; c++) { s.pr[c] = s.lr[c]; s.pi[c] = s.li[c]; csq(s.pr[c], s.pi[c]); csq(s.pr[c], s.pi[c]); csq(s.pr[c], s.pi[c]); csq(s.pr[c], s.pi[c]); }
}
DEVI void scan_quad(Scan& s, uint32_t* w, float4* dst, int q, uint32_t tag) {
#pragma unroll
  for (int c = 0; c < 2; c++) {
    float r = __shfl_up_sync(0xffffffffu, s.hr[c], 1, 4), i = __shfl_up_sync(0xffffffffu, s.hi[c], 1, 4);
    if (q < 1) { r = 0.f; i = 0.f; }
    s.hr[c] = fmaf(s.pr[c], r, fmaf(-s.pi[c], i, s.hr[c])); s.hi[c] = fmaf(s.pr[c], i, fmaf(s.pi[c], r, s.hi[c]));
    w[W_Q + 2 * c] = fu((q & 1) ? s.pr[c] : 1.f); w[W_Q + 2 * c + 1] = fu((q & 1) ? s.pi[c] : 0.f);
    csq(s.pr[c], s.pi[c]);
    r = __shfl_up_sync(0xffffffffu, s.hr[c], 2, 4); i = __shfl_up_sync(0xffffffffu, s.hi[c], 2, 4);
    if (q < 2) { r = 0.f; i = 0.f; }
    s.hr[c] = fmaf(s.pr[c], r, fmaf(-s.pi[c], i, s.hr[c])); s.hi[c] = fmaf(s.pr[c], i, fmaf(s.pi[c], r, s.hi[c]));
  }
  if (q == 3) asm volatile("st.relaxed.gpu.global.v4.b32 [%0], {%1,%2,%3,%4};" :: "l"(dst), "r"((fu(s.hr[0]) & ~1u) | tag), "r"(fu(s.hi[0])), "r"(fu(s.hr[1])), "r"(fu(s.hi[1])) : "memory");
}
DEVI void scan_excl(Scan& s, uint32_t* w, int q) {
#pragma unroll
  for (int c = 0; c < 2; c++) {
    const float r = __shfl_up_sync(0xffffffffu, s.hr[c], 1, 4), i = __shfl_up_sync(0xffffffffu, s.hi[c], 1, 4);
    s.hr[c] = q < 1 ? 0.f : r; s.hi[c] = q < 1 ? 0.f : i;
    float qr = uf(w[W_Q + 2 * c]), qi = uf(w[W_Q + 2 * c + 1]);
    if (q & 2) cmul(qr, qi, s.pr[c], s.pi[c]);
    w[W_Q + 2 * c] = fu(qr); w[W_Q + 2 * c + 1] = fu(qi);
    csq(s.pr[c], s.pi[c]);
  }
}
DEVI void scan_powf(Scan& s, uint32_t* w, int q) {
#pragma unroll
  for (int c = 0; c < 2; c++) {
    float r = s.pr[c], i = s.pi[c]; csq(r, i); csq(r, i); csq(r, i);
    float fr = (q & 1) ? 1.f : r, fi = (q & 1) ? 0.f : i;
    csq(r, i);
    if (!(q & 2)) cmul(fr, fi, r, i);
    w[W_F + 2 * c] = fu(fr); w[W_F + 2 * c + 1] = fu(fi);
  }
}
template <int H, int L = W_L> DEVI void scan_reld(uint32_t* w, const float4* st, int p0, int q) {
  asm volatile("" : "+l"(st), "+r"(p0));
  st += (8 * q - 32) * 32;
#pragma unroll
  for (int k = 0; k < 4; k++) {
    uint32_t* v = w + L + 4 * k;
    asm volatile("{\n.reg .pred p;\nsetp.ge.s32 p, %5, %6;\n@p ld.relaxed.gpu.global.v4.u32 {%0,%1,%2,%3}, [%4];\n}"
                 : "+r"(v[0]), "+r"(v[1]), "+r"(v[2]), "+r"(v[3]) : "l"(st + (4 * H + k) * 32), "r"(p0), "r"(-4 * H - k) : "memory");
  }
}
template <int H, int L = W_L> DEVI void scan_gld(uint32_t* w, const float4* st, int p0, int q, uint32_t tag) {
#pragma unroll
  for (int k = 0; k < 16; k++) w[L + k] = k & 3 ? 0 : tag;
  scan_reld<H, L>(w, st, p0, q);
}
template <int H, int L = W_L> DEVI void scan_chk(uint32_t& c, uint32_t* w, const float4* st, int p0, int q, uint32_t tag) {
#pragma unroll 1
  while (__any_sync(0xffffffffu, ((w[L] ^ tag) | (w[L + 4] ^ tag) | (w[L + 8] ^ tag) | (w[L + 12] ^ tag)) & 1) && ++c < SPIN_MAX) scan_reld<H, L>(w, st, p0, q);
}
template <int H, int L = W_L> DEVI void scan_horner(Scan& s, uint32_t* w) {
#pragma unroll
  for (int k = 0; k < 4; k++)
#pragma unroll
    for (int c = 0; c < 2; c++) {
      const float vr = uf(w[L + 4 * k + 2 * c]), vi = uf(w[L + 4 * k + 2 * c + 1]);
      const float gr = uf(w[W_G + 2 * c]), gi = uf(w[W_G + 2 * c + 1]);
      if (H == 0 && k == 0) { w[W_G + 2 * c] = fu(vr); w[W_G + 2 * c + 1] = fu(vi); }
      else { w[W_G + 2 * c] = fu(fmaf(s.pr[c], gr, fmaf(-s.pi[c], gi, vr))); w[W_G + 2 * c + 1] = fu(fmaf(s.pr[c], gi, fmaf(s.pi[c], gr, vi))); }
    }
}
DEVI void scan_carry(Scan& s, uint32_t* w) {
#pragma unroll
  for (int c = 0; c < 2; c++) {
    float gr = uf(w[W_G + 2 * c]), gi = uf(w[W_G + 2 * c + 1]);
    const float qr = uf(w[W_Q + 2 * c]), qi = uf(w[W_Q + 2 * c + 1]);
    cmul(gr, gi, uf(w[W_F + 2 * c]), uf(w[W_F + 2 * c + 1]));
    gr += __shfl_xor_sync(0xffffffffu, gr, 1); gi += __shfl_xor_sync(0xffffffffu, gi, 1);
    gr += __shfl_xor_sync(0xffffffffu, gr, 2); gi += __shfl_xor_sync(0xffffffffu, gi, 2);
    s.hr[c] = fmaf(qr, gr, fmaf(-qi, gi, s.hr[c])); s.hi[c] = fmaf(qr, gi, fmaf(qi, gr, s.hi[c]));
  }
}
template <int JJ, bool W4 = false> DEVI void scan_p2(Scan& s, uint32_t (&keep)[4], const float (&ur)[32], const float (&ui)[32], uint32_t* dst, bool odd, uint32_t* k2 = nullptr, bool hi = false) {
#pragma unroll
  for (int c = 0; c < 2; c++) {
    float o_r[2], o_i[2];
#pragma unroll
    for (int e = 0; e < 2; e++) {
      const int a = 4 * JJ + 2 * c + e;
      const float tr = fmaf(s.lr[c], s.hr[c], ur[a]), ti = fmaf(s.lr[c], s.hi[c], ui[a]);
      const float nr = fmaf(-s.li[c], s.hi[c], tr); s.hi[c] = fmaf(s.li[c], s.hr[c], ti); s.hr[c] = nr;
      o_r[e] = fmaf(s.cr[c], s.hr[c], -s.ci[c] * s.hi[c]); o_i[e] = fmaf(-s.cr[c], s.hi[c], -s.ci[c] * s.hr[c]);
    }
#pragma unroll
    for (int m = 0; m < 2; m++) {
      const uint32_t v = m ? pack2(o_i[0], o_i[1]) : pack2(o_r[0], o_r[1]);
      if constexpr ((JJ & 1) == 0) keep[2 * c + m] = v;
      else {
        const uint32_t k = keep[2 * c + m], rv = __shfl_xor_sync(0xffffffffu, odd ? k : v, 1);
        const uint32_t b0 = odd ? rv : k, b1 = odd ? v : rv;
        if constexpr (!W4) asm volatile("st.global.v2.b32 [%0], {%1,%2};" :: "l"(dst + (m * DM + c * 8) * (SEQ / 2) + 4 * (JJ - 1)), "r"(b0), "r"(b1) : "memory");
        else if constexpr (!(JJ & 2)) { k2[4 * c + 2 * m] = b0; k2[4 * c + 2 * m + 1] = b1; }
        else {
          const uint32_t a0 = k2[4 * c + 2 * m], a1 = k2[4 * c + 2 * m + 1];
          const uint32_t r0 = __shfl_xor_sync(0xffffffffu, hi ? a0 : b0, 2), r1 = __shfl_xor_sync(0xffffffffu, hi ? a1 : b1, 2);
          asm volatile("st.global.v4.b32 [%0], {%1,%2,%3,%4};" :: "l"(dst + (m * DM + c * 8) * (SEQ / 2) + 4 * (JJ - 3)), "r"(hi ? r0 : a0), "r"(hi ? r1 : a1), "r"(hi ? b0 : r0), "r"(hi ? b1 : r1) : "memory");
        }
      }
    }
  }
}
DEVI void pin_s(Scan& s) { pin(s.hr); pin(s.hi); pin(s.pr); pin(s.pi); }
template <int A, int N> DEVI void pin_w(uint32_t* w) {
#pragma unroll
  for (int i = A; i < A + N; i++) asm volatile("" : "+r"(w[i]) :: "memory");
}

DEVI float silu_h(float v) {
  float t;
  asm("tanh.approx.f32 %0, %1;" : "=f"(t) : "f"(v));
  return fmaf(v, t, v);
}
template <int A0, int A1> DEVI void epi_silu(float (&z)[32], const uint32_t (&zr)[16]) {
#pragma unroll
  for (int a = A0; a < A1; a++) {
    z[a] = silu_h(z[a] + ((a & 1) ? bhi(zr[a >> 1]) : blo(zr[a >> 1])));
    asm volatile("" : "+f"(z[a]) :: "memory");
  }
}
template <int JJ, bool MUL> DEVI void epi_x(float (&t)[32], const uint32_t* dh, uint32_t xa) {
  uint32_t xv[4];
  ldsm4(xv, xa ^ (JJ << 4));
#pragma unroll
  for (int p = 0; p < 4; p++) {
    if constexpr (MUL) xv[p] = hmul2(xv[p], dh[JJ + (p >> 1)]);
    const int a = 4 * JJ + 2 * p;
    t[a] = blo(xv[p]); t[a + 1] = bhi(xv[p]);
    asm volatile("" : "+f"(t[a]), "+f"(t[a + 1]) :: "memory");
  }
}
DEVI void epi_store(float* o, const float (&t)[32], const float (&g)[32], const float (&y)[32]) {
#pragma unroll
  for (int jj = 0; jj < 8; jj++)
#pragma unroll
    for (int r = 0; r < 2; r++) {
      const int a = 4 * jj + 2 * r;
      asm volatile("st.global.v2.f32 [%0], {%1,%2};" :: "l"(o + r * 2 * DM + 8 * jj), "f"(fmaf(g[a], y[a], t[a])), "f"(fmaf(g[a + 1], y[a + 1], t[a + 1])) : "memory");
    }
}
template <int N> DEVI void epi_store4(float* o, const float (&t)[32], const float (&g)[32], const float (&y)[32], bool odd) {
#pragma unroll
  for (int jj = 0; jj < N; jj += 2)
#pragma unroll
    for (int r = 0; r < 2; r++) {
      float v[4];
#pragma unroll
      for (int k = 0; k < 4; k++) { const int a = 4 * jj + 2 * r + (k & 1) + 4 * (k >> 1); v[k] = fmaf(g[a], y[a], t[a]); }
      const float r0 = __shfl_xor_sync(0xffffffffu, odd ? v[0] : v[2], 1), r1 = __shfl_xor_sync(0xffffffffu, odd ? v[1] : v[3], 1);
      asm volatile("st.global.v4.f32 [%0], {%1,%2,%3,%4};" :: "l"(o + r * 2 * DM + 8 * jj), "f"(odd ? r0 : v[0]), "f"(odd ? r1 : v[1]), "f"(odd ? v[2] : r0), "f"(odd ? v[3] : r1) : "memory");
    }
}
DEVI void ldg4(uint32_t* r, const void* p) {
  asm volatile("ld.relaxed.gpu.global.v4.u32 {%0,%1,%2,%3}, [%4];" : "=r"(r[0]), "=r"(r[1]), "=r"(r[2]), "=r"(r[3]) : "l"(p) : "memory");
}
DEVI void lds4(uint32_t* r, uint32_t addr) {
  asm volatile("ld.shared.v4.b32 {%0,%1,%2,%3}, [%4];" : "=r"(r[0]), "=r"(r[1]), "=r"(r[2]), "=r"(r[3]) : "r"(addr) : "memory");
}
template <uint32_t SB> DEVI void epi_store_s(float* o, const float (&t)[32], const float (&g)[32], const float (&y)[32], uint32_t s, int lane) {
  const uint32_t w = s + (lane >> 2) * 128 + (lane & 15) * 8, r = s + (lane >> 3) * 128 + ((lane * 16 ^ lane * 4) & 96) + (lane & 1) * 16;
  o += ((lane & 16) + ((lane >> 3) & 1)) * DM + (lane & 7) * 4;
#pragma unroll
  for (int h = 0; h < 2; h++) {
#pragma unroll
    for (int k = 0; k < 8; k++) {
      const int a = 16 * h + 2 * k;
      asm volatile("st.shared.v2.f32 [%0], {%1,%2};" :: "r"((w ^ (k >> 1) * 32) + (k & 1) * 1024 + h * SB), "f"(fmaf(g[a], y[a], t[a])), "f"(fmaf(g[a + 1], y[a + 1], t[a + 1])) : "memory");
    }
    __syncwarp();
#pragma unroll
    for (int m = 0; m < 4; m++) {
      uint32_t v[4];
      lds4(v, r + m * 512 + h * SB);
      asm volatile("st.global.v4.b32 [%0], {%1,%2,%3,%4};" :: "l"(o + (32 * (m & 1) + (m & 2)) * DM + 32 * h), "r"(v[0]), "r"(v[1]), "r"(v[2]), "r"(v[3]) : "memory");
    }
  }
}
DEVI int blk_of(int j, int b) { return b == 0 ? 8 : ((j + b) & 7); }

constexpr uint32_t UNIT = 24576;
#define NC1 6
#define ZT 21
#define ZN 3
#define ZK 4
#define PFP 400
#define ST4 5
#define ER 2
#define NP3 1
#define LW 496
#define LB 1
#define SM 0
#define SU 1
#define SPOS 4
#define BPF 400
#define EPF 3
#define PWAIT mbar_wait
#define ZW B_XN
#define ZS 3000
#define ZP 200
#define Z32 0
#define HS4 0
#define STAG 1
#define PFX 1
#define SCHED 4, 4, 5, 6, 9, 12, 15, 16, 18
__device__ constexpr uint32_t SCH[9] = {SCHED};
struct Ring { uint32_t o, ph; };
DEVI void ring_next(Ring& r) { r.o += 8; if (r.o == 40) { r.o = 0; r.ph ^= 1; } }

DEVI void spare_consumer(const Params& P, uint32_t sb, int warp, int lane) {
  const uint32_t tag = ld_epoch() & 1;
  const int wg = warp >> 2, w = warp & 3, g = lane >> 2, q = lane & 3, sp = blockIdx.x - 128;
  const uint32_t bar = sb + OFF_BAR, rb = bar + 40 * wg;
  const uint64_t d0 = P.desc + ((sb & 0x3FFFF) >> 4), dr = d0 + 9 * 1024 + wg * 512;
  uint32_t c = 0, prev = 0;
  Ring rg = {0, 0};
  Scan s;
  scan_load(s, sb + OFF_PAR + (16 * w + g) * 16);
  if (wg) asm volatile("bar.sync 1, 256;" ::: "memory");
  mbar_wait(c, bar + 8 * B_RES, 0);
#pragma unroll 1
  for (int r = 0; r < 4; r++) {
    float ur[32], ui[32];
    uint32_t wk[48], keep[4];
#pragma unroll 1
    for (int u = 0; u < 9; u++) {
      mbar_wait(c, rb + 8 * B_FULL + rg.o, rg.ph);
      wg_fence();
      const uint64_t a = d0 + u * 1024, b = dr + rg.o * 128;
      wg_ss64p<0, 0, 0, 0>(ur, a, b, u); wg_ss64p<0, 0, 512, 0>(ui, a, b, u);
      sfor<1, 4>([&](auto K) { wg_ss64<0, 0, 2 * K.v, 2 * K.v>(ur, a, b); wg_ss64<0, 0, 512 + 2 * K.v, 2 * K.v>(ui, a, b); });
      wg_commit();
      wg_wait<1>();
      mbar_arrive_warp_if(rb + 8 * B_EMPTY + prev, u);
      prev = rg.o;
      ring_next(rg);
    }
    wg_wait<0>();
    mbar_arrive_warp(rb + 8 * B_EMPTY + prev);
    mbar_arrive_warp_if(bar + 8 * B_XN, r == 3);
    if (r + wg == 0) asm volatile("bar.arrive 1, 256;" ::: "memory");
    pin(ur); pin(ui);
    TRC(1 + 4 * r);
    const int seg = 8 * r + 4 * wg + sp;
    float4* stp = g_state + 8 * 1024 + seg * 32 + w * 8 + g;
    uint32_t* hsp = (uint32_t*)g_hsT + (size_t)(512 + 16 * w + g) * (SEQ / 2) + seg * 32 + (q & 1) * 4 + (q & 2);
    scan_pow16(s);
    scan_p1<0, 16>(s, ur, ui);
    scan_quad(s, wk, stp, q, tag);
    scan_gld<0>(wk, stp, seg - 32 + 8 * q, q, tag);
    scan_excl(s, wk, q); scan_powf(s, wk, q);
    scan_gld<1, 32>(wk, stp, seg - 32 + 8 * q, q, tag);
    TRC(2 + 4 * r);
    scan_chk<0>(c, wk, stp, seg - 32 + 8 * q, q, tag); scan_horner<0>(s, wk);
    scan_chk<1, 32>(c, wk, stp, seg - 32 + 8 * q, q, tag); scan_horner<1, 32>(s, wk);
    TRC(3 + 4 * r);
    scan_carry(s, wk);
#pragma unroll 1
    for (int k = 0; k < 4; k++, hsp += 8) {
      scan_p2<0>(s, keep, ur, ui, hsp, q & 1); scan_p2<1>(s, keep, ur, ui, hsp, q & 1);
#pragma unroll
      for (int i = 0; i < 24; i++) { ur[i] = ur[i + 8]; ui[i] = ui[i + 8]; }
    }
    __syncwarp(); mbar_arrive_warp(bar + 8 * (B_HS + wg));
    TRC(4 + 4 * r);
  }
  float y[4][32];
  rg.o = 0; rg.ph = 0;
#pragma unroll 1
  for (int u = 0; u < 18; u++) {
    mbar_wait(c, bar + 8 * B_XT + rg.o, rg.ph);
    wg_fence();
    const uint64_t b = d0 + rg.o * 576, a = b + wg * 512;
    sfor<0, 4>([&](auto R) {
      constexpr uint32_t o = R.v * 1024;
      wg_ss64p<1, 0, o, 4096>(y[R.v], a, b, u); wg_ss64<1, 0, o + 128, 4098>(y[R.v], a, b); wg_ss64<1, 0, o + 256, 4100>(y[R.v], a, b); wg_ss64<1, 0, o + 384, 4102>(y[R.v], a, b);
    });
    wg_commit();
    wg_wait<0>();
    mbar_arrive_warp(bar + 8 * (B_XN + 1) + rg.o);
    rg.o += 8; if (rg.o == 24) { rg.o = 0; rg.ph ^= 1; }
  }
  TRC(22);
  uint32_t dh[8], lsm = sb + wg * 8192 + (16 * w + (lane & 15)) * 128 + (((lane >> 4) ^ (lane & 7)) << 4), za = sb + 147456 + warp * 2048 + lane * 16;
  float* op = P.out + (size_t)((4 * wg + sp) * 64 + 4 * w) * DM + 512;
  lds4(dh, sb + OFF_D + q * 32); lds4(dh + 4, sb + OFF_D + q * 32 + 16);
#pragma unroll
  for (int k = 0; k < 3; k++) mbar_wait(c, bar + 8 * (B_XT + k), 0);
#pragma unroll
  for (int r = 0; r < 4; r++) pin(y[r]);
#pragma unroll 1
  for (int r = 0; r < 4; r++, lsm += SLOT, za += SLOT, op += 512 * DM) {
    float t[32], z[32];
    uint32_t zr[16];
#pragma unroll
    for (int k = 0; k < 4; k++) lds4(&zr[4 * k], za + k * 512);
    sfor<0, 4>([&](auto K) { epi_x<2 * K.v, true>(t, dh, lsm); });
#pragma unroll
    for (int k = 0; k < 32; k++) { y[0][k] += t[k]; z[k] = silu_h(k & 1 ? bhi(zr[k >> 1]) : blo(zr[k >> 1])); }
    sfor<0, 4>([&](auto K) { epi_x<2 * K.v, false>(t, nullptr, lsm + 73728); });
    epi_store_s<73728>(op, t, z, y[0], za - 147456 - lane * 16, lane);
#pragma unroll
    for (int k = 0; k < 96; k++) y[k >> 5][k & 31] = y[(k >> 5) + 1][k & 31];
  }
  TRC(23);
  spin_check(c);
}

template <int T, int R0 = 0, int R1 = 16> DEVI void tile_end(uint32_t (&h)[144], float (&acc)[64]) {
  if constexpr (R0 == 0) pin(acc);
#pragma unroll
  for (int r = R0; r < R1; r++) {
    h[16 * T + r] = pack2(acc[2 * r] * acc[32 + 2 * r] * 0.5f, acc[2 * r + 1] * acc[33 + 2 * r] * 0.5f);
    asm volatile("" : "+r"(h[16 * T + r]) :: "memory");
  }
}

#define IDS const int tx = tid_x(), lane = tx & 31, warp = tx >> 5, w = warp & 3, g = lane >> 2, q = lane & 3; (void)w; (void)g; (void)q
DEVI void main_consumer(const Params& P, uint32_t sb, int wg, int mi, int j) {
  if (!(VP & 2)) { j = CJ(blockIdx.x); mi = CM(blockIdx.x); }
  const uint32_t bar = sb + OFF_BAR;
  uint32_t rbar;
  asm("mapa.shared::cluster.u32 %0, %1, %2;" : "=r"(rbar) : "r"(bar), "r"(~blockIdx.x & 1));
  uint64_t d0 = P.desc + ((sb & 0x3FFFF) >> 4), dx = d0 + wg * 512;
  uint32_t c = 0, h[144];
  Ring rg = {32, 1};
  uint32_t prev = 24;
  {
    float acc[64];
    Scan s;
    {
      IDS;
      constexpr int NKEEP = 8;
      uint32_t xv[144], one[8];
      float d[2][4][4];
#pragma unroll
      for (int k = 0; k < 32; k++) (&d[0][0][0])[k] = 0.f;
#pragma unroll
      for (int k = 0; k < 8; k++) one[k] = __shfl_sync(0xffffffffu, lane < 8 ? 0x3f803f80u : 0u, k);
      const uint32_t la = sb + (16 * warp + (lane & 7) + 8 * (lane >> 4)) * 128 + ((((lane >> 3) & 1) ^ (lane & 7)) << 4);
      const uint32_t sa = sb + (16 * warp + (lane & 15)) * 128 + (((lane >> 4) ^ (lane & 7)) << 4);
#pragma unroll
      for (int u = 0; u < 9; u++) {
        if (u % 3 == 0) { mbar_wait(c, bar + 8 * (B_X0 + u / 3) + 24 * wg, 0); TRC(144 + u / 3); }
#pragma unroll
        for (int k = 0; k < 4; k++) ldsm4(&xv[16 * u + 4 * k], (la ^ (k << 5)) + u * SLOT);
#pragma unroll
        for (int k = 0; k < 4; k++)
#pragma unroll
          for (int r = 0; r < 2; r++) {
            const uint32_t v0 = xv[16 * u + 4 * k + 2 * r], v1 = xv[16 * u + 4 * k + 2 * r + 1];
            mma16816(d[r][k], v0, one[4 * r + 2 * (k & 1)], v1, one[4 * r + 2 * (k & 1) + 1], v0, v1);
          }
      }
      mbar_wait(c, bar + 8 * B_FULL, 0);
      TRC(140);
      const int src = 4 * g + (g >> 1);
      uint32_t rh2[2], rl2[2], c2[2];
#pragma unroll
      for (int r = 0; r < 2; r++) {
#pragma unroll
        for (int k = 0; k < 4; k++) d[r][0][k] = (d[r][0][k] + d[r][1][k]) + (d[r][2][k] + d[r][3][k]);
        float ss = (g & 1) ? d[r][0][1] : d[r][0][0], sm = (g & 1) ? d[r][0][3] : d[r][0][2];
        ss = __shfl_sync(0xffffffffu, ss, src); sm = __shfl_sync(0xffffffffu, sm, src);
        const float mean = sm * (1.0f / DM);
        const float var = fmaxf(fmaf(-mean, mean, ss * (1.0f / DM)), 0.f);
        float sd, rs;
        asm("sqrt.approx.f32 %0, %1;" : "=f"(sd) : "f"(bhi(pack2(0.f, bhi(pack2(0.f, var)) + 1e-5f))));
        asm("rcp.approx.f32 %0, %1;" : "=f"(rs) : "f"(bhi(pack2(0.f, sd))));
        rh2[r] = pack2(rs, rs);
        const float rl = rs - bhi(rh2[r]), cc = -bhi(pack2(0.f, mean)) * rs;
        rl2[r] = pack2(rl, rl); c2[r] = pack2(cc, cc);
      }
      auto norm = [&](auto U) {
#pragma unroll
        for (int k = 0; k < 4; k++) {
          uint32_t* v = &xv[16 * U.v + 4 * k];
          const uint32_t t1 = U.v < NKEEP ? v[2] : v[1], t2 = U.v < NKEEP ? v[1] : v[2];
          v[0] = hfma2(v[0], rh2[0], hfma2(v[0], rl2[0], c2[0])); v[1] = hfma2(t1, rh2[1], hfma2(t1, rl2[1], c2[1]));
          v[2] = hfma2(t2, rh2[0], hfma2(t2, rl2[0], c2[0])); v[3] = hfma2(v[3], rh2[1], hfma2(v[3], rl2[1], c2[1]));
          stsm4((sa ^ (k << 5)) + U.v * SLOT, v);
        }
      };
      norm(IC<0>{});
      TRC(0); TRG(160);
      sfor<0, 9>([&](auto U) {
        constexpr uint32_t u = U.v, b = (9 + u % 5) * 1024;
        if constexpr (u == 5) d0 = fresh(d0, c);
        wg_fence();
        if constexpr (u == 0) wg_rs128z<1, b>(acc, &xv[16 * u], d0); else wg_rs128<1, b>(acc, &xv[16 * u], d0);
        wg_rs128<1, b + 128>(acc, &xv[16 * u + 4], d0);
        if constexpr (u > 0 && u <= ER) { wg_commit(); wg_wait<1>(); mbar_arrive2(bar, rbar, 8 * (B_EMPTY + (u - 1) % 5)); }
        if constexpr (u + 1 >= NKEEP && u < 8) {
#pragma unroll
          for (int k = 0; k < 4; k++) ldsm4(&xv[16 * u + 16 + 4 * k], (sa ^ (k << 5)) + (u + 1) * SLOT);
        }
        if constexpr (u == 8) {
          fence_async_smem();
          if (wg == 0) asm volatile("bar.sync 1, 128;" ::: "memory"); else asm volatile("bar.sync 2, 128;" ::: "memory");
        }
        if constexpr (u == 1) mbar_arrive_warp(bar + 8 * B_XN);
        if constexpr (u >= NP3) {
          if constexpr (!(LW >> u & 1)) mbar_wait_f(c, bar + 8 * (B_FULL + (u + 1) % 5), ((u + 1) / 5) & 1);
          else if constexpr (LB) mbar_wait_f(c, bar + 8 * (B_FULL + u % 5), (u / 5) & 1);
          if constexpr (u < 8) norm(IC<u + 1>{});
        }
        if constexpr (u == 8) { scan_load(s, sb + OFF_PAR + ((tid_x() & 96) * 2 + (tid_x() & 28)) * 4); scan_pow16(s); pin(s.pr); pin(s.pi); }
        wg_rs128<1, b + 256>(acc, &xv[16 * u + 8], d0);
        if constexpr (u > ER) { wg_commit(); wg_wait<1>(); mbar_arrive2(bar, rbar, 8 * (B_EMPTY + (u - 1) % 5)); }
        wg_rs128<1, b + 384>(acc, &xv[16 * u + 12], d0);
        wg_commit();
        if constexpr (LW >> u & 1) mbar_wait(c, bar + 8 * (B_FULL + (u + 1) % 5), ((u + 1) / 5) & 1);
        if constexpr (u < NP3) {
          mbar_wait(c, bar + 8 * (B_FULL + (u + 1) % 5), ((u + 1) / 5) & 1);
          norm(IC<u + 1>{});
        }
      });
    }
    TRC(9);
    float ur[32], ui[32];
#pragma unroll 1
    for (int u = 0; u < 9; u++) {
      wg_fence();
      const uint64_t a = d0 + 9 * 1024 + rg.o * 128, b = dx + u * 1024;
      wg_ss64p<0, 0, 0, 0>(ur, a, b, u); wg_ss64p<0, 0, 512, 0>(ui, a, b, u);
      wg_ss64<0, 0, 2, 2>(ur, a, b); wg_ss64<0, 0, 514, 2>(ui, a, b);
      wg_commit();
      wg_wait<1>();
      mbar_arrive2(bar, rbar, 8 * B_EMPTY + prev);
      prev = rg.o;
      ring_next(rg);
      wg_ss64<0, 0, 4, 4>(ur, a, b); wg_ss64<0, 0, 516, 4>(ui, a, b);
      mbar_wait_f(c, bar + 8 * B_FULL + rg.o, rg.ph);
      wg_ss64<0, 0, 6, 6>(ur, a, b); wg_ss64<0, 0, 518, 6>(ui, a, b);
      wg_commit();
    }
    tile_end<0>(h, acc);
    TRC(18); TRG(161);
    IDS;
    const uint32_t tag = ld_epoch() & 1;
    const int seg = mi * 2 + wg;
    float4* stp = g_state + j * 1024 + seg * 32 + w * 8 + g;
    uint32_t* hsp = (uint32_t*)g_hsT + (size_t)(j * 64 + 16 * w + g) * (SEQ / 2) + seg * 32 + (HS4 ? q * 4 : (q & 1) * 4 + (q & 2));
    uint32_t wk[32], keep[4], k2[8];
    sfor<1, 4>([&](auto T) {
      constexpr int t = T.v;
      sfor<0, 9>([&](auto U) {
        constexpr uint32_t u = U.v, S = 9 + 9 * t + u, sg = S - 18, a = u * 1024, b = (9 + S % 5) * 1024;
        if constexpr (u == 0 && (SM >> t & 1)) asm volatile("{\n.reg .pred p;\nsetp.ne.b32 p, %0, 0;\n@p bar.sync 5, 256;\n}" :: "r"(wg) : "memory");
        if constexpr (u == 0) dx = fresh(dx, c);
        if constexpr (sg % 5 == 0) d0 = fresh(d0, c);
        if constexpr (u == 0) { wg_fence(); wg_ss128p<0, 1, a, b>(acc, dx, d0, (int)P.desc & 1); }
        else wg_ss128<0, 1, a, b>(acc, dx, d0);
        wg_ss128<0, 1, a + 2, b + 128>(acc, dx, d0);
        wg_commit();
        mbar_wait_f(c, bar + 8 * (B_FULL + (S + 1) % 5), ((S + 1) / 5) & 1);
        wg_ss128<0, 1, a + 4, b + 256>(acc, dx, d0);
        wg_commit();
        if constexpr (u > 0 || t == 1) { wg_wait<2>(); mbar_arrive2(bar, rbar, 8 * (B_EMPTY + (S - 1) % 5)); }
        if constexpr (u == SU && (SM >> t & 1)) asm volatile("{\n.reg .pred p;\nsetp.eq.b32 p, %0, 0;\n@p bar.arrive 5, 256;\n}" :: "r"(wg) : "memory");
        wg_ss128<0, 1, a + 6, b + 384>(acc, dx, d0);
        wg_commit();
        if constexpr (sg == 0) { pin(ur); pin(ui); } else pin_s(s);
        if constexpr (sg < SCH[0]) scan_p1<(16 * sg + SCH[0] - 1) / SCH[0], (16 * sg + 15 + SCH[0]) / SCH[0]>(s, ur, ui);
        if constexpr (sg == SCH[1]) { scan_quad(s, wk, stp, q, tag); pin_w<W_Q, 4>(wk); }
        if constexpr (sg == SCH[2]) { scan_excl(s, wk, q); pin_w<W_Q, 4>(wk); }
        if constexpr (sg == SCH[3]) { scan_powf(s, wk, q); pin_w<W_F, 4>(wk); }
        if constexpr (sg == SCH[4]) scan_gld<0>(wk, stp, seg - 32 + 8 * q, q, tag);
        if constexpr (sg == SCH[5]) {
          scan_chk<0>(c, wk, stp, seg - 32 + 8 * q, q, tag); wg_fence();
          scan_horner<0>(s, wk); pin_w<W_G, 4>(wk); scan_gld<1>(wk, stp, seg - 32 + 8 * q, q, tag);
        }
        if constexpr (sg == SCH[6]) { scan_chk<1>(c, wk, stp, seg - 32 + 8 * q, q, tag); wg_fence(); scan_horner<1>(s, wk); pin_w<W_G, 4>(wk); }
        if constexpr (sg == SCH[7]) { pin_w<W_G, 4>(wk); scan_carry(s, wk); }
        if constexpr (sg >= SCH[8] && sg < SCH[8] + 8) { scan_p2<sg - SCH[8], HS4>(s, keep, ur, ui, hsp, q & 1, k2, q & 2); if constexpr (!((sg - SCH[8]) & 1)) pinu(keep); if constexpr (HS4 && ((sg - SCH[8]) & 3) == 1) pinu(k2); }
        if constexpr (sg == SCH[8] + 7) { __syncwarp(); mbar_arrive_warp(bar + 8 * (B_HS + wg)); }
        if constexpr (sg < SCH[8] + 7) pin_s(s);
      });
      wg_wait<0>();
      mbar_arrive2(bar, rbar, 8 * (B_EMPTY + (17 + 9 * t) % 5));
      tile_end<t>(h, acc);
      TRC(18 + 9 * t);
    });
  }
  TRG(162);
  rg.o = 0; rg.ph = 1;
  float y[32], z[32];
  auto go = [&](int u, int at) { asm volatile("{\n.reg .pred p;\nsetp.eq.b32 p, %0, %1;\n@p bar.arrive 5, 256;\n}" :: "r"(u + 16 * wg), "r"(at) : "memory"); };
  sfor<4, 9>([&](auto T) {
    float acc[64];
    if (wg) asm volatile("bar.sync 5, 256;" ::: "memory");
#pragma unroll 1
    for (int u = 0; u < 9; u++) {
      wg_fence();
      const uint64_t a = dx + u * 1024, b = d0 + 9 * 1024 + rg.o * 128;
      wg_ss128p<0, 1, 0, 0>(acc, a, b, u); wg_ss128<0, 1, 2, 128>(acc, a, b);
      wg_commit();
      if constexpr (SPOS == 1) go(u, 1);
      const uint32_t cur = rg.o;
      ring_next(rg);
      mbar_wait_f(c, bar + 8 * B_FULL + rg.o, rg.ph);
      wg_ss128<0, 1, 4, 256>(acc, a, b);
      wg_commit();
      wg_wait<2>();
      mbar_arrive2(bar, rbar, 8 * B_EMPTY + prev, u);
      if constexpr (SPOS == 0 || SPOS == 3) go(u, SPOS == 0);
      prev = cur;
      wg_ss128<0, 1, 6, 384>(acc, a, b);
      wg_commit();
      if constexpr (SPOS == 2) go(u, 0);
      if constexpr (SPOS == 4) go(u, 1);
    }
    wg_wait<0>();
    mbar_arrive2(bar, rbar, 8 * B_EMPTY + prev);
    tile_end<T.v>(h, acc);
    TRC(18 + 9 * T.v);
  });
  TRG(163);
  auto down = [&](auto I, uint64_t db, uint32_t bo, uint32_t ph, auto&& extra) {
    constexpr int i = I.v;
    sfor<0, 12>([&](auto K) {
      constexpr uint32_t k = K.v, ob = i * (UNIT / 16) + k * 128;
      if constexpr (k == 0 && i < 2) wg_fence();
      if constexpr (i == 0 && k == 0) wg_rs64z<1, ob>(z, &h[0], db); else wg_rs64<1, ob>(z, &h[48 * i + 4 * k], db);
      if constexpr (k == 4) {
        wg_commit();
        wg_wait<1>();
        mbar_arrive2(bar, rbar, 8 * (B_EMPTYT + ((i + 3) & 3)) + (i ? bo : bo ^ 32));
      }
      if constexpr (k == 8) mbar_wait_f(c, bar + 8 * (B_FULLT + i + 1) + bo, ph);
      if constexpr (k == 10 && i == 2) mbar_wait_f(c, bar + 8 * B_FULLT + (bo ^ 32), ph ^ (bo >> 5));
      extra(K);
    });
    wg_commit();
  };
  {
    IDS;
    const uint32_t lsm = sb + (16 * warp + (lane & 15)) * 128 + (((lane >> 4) ^ (lane & 7)) << 4);
    uint32_t dh[8];
    mbar_wait_f(c, bar + 8 * B_FULLT, 0);
    sfor<0, 12>([&](auto K) {
      constexpr uint32_t k = K.v;
      if constexpr (k == 0) wg_rs64z<1, 1024>(z, &h[0], d0); else wg_rs64<1, 1024 + k * 128>(z, &h[4 * k], d0);
      if constexpr (k == 1) { lds4(dh, sb + OFF_D + q * 32); lds4(dh + 4, sb + OFF_D + q * 32 + 16); }
      if constexpr (k == 2) mbar_wait_f(c, bar + 8 * (B_FULLT + 1), 0);
      if constexpr (k >= 3 && k < 11 && (k & 1)) epi_x<k - 3, true>(y, dh, lsm);
    });
    wg_commit();
  }
  {
    uint32_t o = 0, ph = 0;
    IDS;
    const uint32_t stg = sb + 13 * SLOT + warp * 2048 + lane * 16;
    uint4* z7 = g_z7 + (mi * 8 + ((j + 7) & 7)) * 1024 + warp * 128 + lane;
#pragma unroll 1
    for (int b = 0; b < 8; b++) {
      const uint64_t db = d0 + 1024 + o * (UNIT / 128);
      down(IC<1>{}, db, o, ph, [&](auto) {});
      down(IC<2>{}, db, o, ph, [&](auto K) { if constexpr (K.v == 6) mbar_wait_f(c, bar + 8 * (B_DF + wg), b & 1); });
      constexpr uint32_t O = 3 * (UNIT / 16);
      const uint64_t da = db + wg * 512;
      wg_ss64<1, 0, O, O + 1024>(y, da, db); wg_ss64<1, 0, O + 128, O + 1026>(y, da, db);
      wg_commit();
      wg_wait<1>();
      pin(z);
      sfor<0, 4>([&](auto K) {
        constexpr int k = K.v;
        asm volatile("{\n.reg .pred p;\nsetp.eq.b32 p, %6, 7;\n@!p st.shared.v4.b32 [%0], {%1,%2,%3,%4};\n@p st.relaxed.gpu.global.v4.b32 [%5], {%1,%2,%3,%4};\n}"
                     :: "r"(stg + k * 512), "r"(pack2(z[8 * k], z[8 * k + 1])), "r"(pack2(z[8 * k + 2], z[8 * k + 3])), "r"(pack2(z[8 * k + 4], z[8 * k + 5])),
                        "r"(pack2(z[8 * k + 6], z[8 * k + 7])), "l"(z7 + k * 32), "r"(b) : "memory");
        if constexpr (k == 1) {
          wg_ss64<1, 0, O + 256, O + 1028>(y, da, db); wg_ss64<1, 0, O + 384, O + 1030>(y, da, db);
          wg_commit();
          mbar_arrive2(bar, rbar, 8 * (B_EMPTYT + 2) + o);
        }
      });
      __syncwarp();
      mbar_arrive_warp(bar + 8 * (B_DR + wg));
      TRC(91 + b);
      ph ^= o >> 5; o ^= 32;
      down(IC<0>{}, d0 + 1024 + o * (UNIT / 128), o, ph, [&](auto) {});
    }
  }
  IDS;
  float tt[32];
  uint32_t zr[16], zl[16];
  const uint32_t lsm = sb + (16 * warp + (lane & 15)) * 128 + (((lane >> 4) ^ (lane & 7)) << 4);
  const size_t orow = (size_t)(mi * 128 + wg * 64 + 16 * (g >> 1) + 4 * w + (g & 1)) * DM + 2 * q;
  const uint4* z7 = g_z7 + (mi * 8 + j) * 1024 + warp * 128 + lane;
  sfor<33, 45>([&](auto TT) {
    constexpr int T = TT.v, i = T - NC1 - 32, nx = T + 1;
    constexpr uint32_t O = 1024 + (T & 7) * (UNIT / 16);
    if constexpr (T == 33 || T == 40) { d0 = fresh(d0, c); dx = fresh(dx, c); }
    if constexpr (i == 1 || i == 2) {
      sfor<0, 12>([&](auto K) {
        constexpr int k = K.v, n = 12 * i - 12 + k;
        wg_rs64<1, O + k * 128>(z, &h[48 * i + 4 * k], d0);
        if constexpr (k == 4) { wg_commit(); wg_wait<1>(); }
        if constexpr (k == 8) mbar_wait_f(c, bar + 8 * (B_FULLT + (nx & 7)), (nx >> 3) & 1);
        if constexpr (n == ZK) {
#pragma unroll
          for (int m = 0; m < 4; m++) ldg4(&zl[4 * m], z7 + m * 32);
        }
        if constexpr (n == 16) mbar_wait_f(c, bar + 8 * (B_XT + wg), 0);
        if constexpr (n > 16 && n <= 20) epi_x<2 * n - 34, false>(tt, nullptr, lsm);
        if constexpr (n == ZT) {
          TRC(10);
          mbar_wait_f(c, bar + 8 * (B_Z + wg), 0);
          TRC(11);
#pragma unroll
          for (int m = 0; m < 4; m++) lds4(&zr[4 * m], sb + 13 * SLOT + warp * 2048 + lane * 16 + m * 512);
        }
      });
      wg_commit();
    } else {
      wg_ss64<1, 0, O, O + 1024>(y, dx, d0); wg_ss64<1, 0, O + 128, O + 1026>(y, dx, d0);
      if constexpr (T < 38 || i == 3) { wg_commit(); wg_wait<1>(); }
      if constexpr (T < 38) mbar_arrive2(bar, rbar, 8 * (B_EMPTYT + ((T - 1) & 7)));
      if constexpr (T < 44) mbar_wait_f(c, bar + 8 * (B_FULLT + (nx & 7)), (nx >> 3) & 1);
      if constexpr (i - 1 == ZK && i < 1) {
#pragma unroll
        for (int m = 0; m < 4; m++) ldg4(&zl[4 * m], z7 + m * 32);
      }
      wg_ss64<1, 0, O + 256, O + 1028>(y, dx, d0); wg_ss64<1, 0, O + 384, O + 1030>(y, dx, d0);
      wg_commit();
    }
    if constexpr (i == 2) {
#pragma unroll 1
      while (__any_sync(0xffffffffu, zl[0] == ~0u || zl[4] == ~0u || zl[8] == ~0u || zl[12] == ~0u) && ++c < SPIN_MAX) {
#pragma unroll
        for (int m = 0; m < 4; m++) ldg4(&zl[4 * m], z7 + m * 32);
        TRC(13);
      }
      TRC(12);
      wg_fence();
#pragma unroll
      for (int m = 0; m < 16; m++) zr[m] = hadd2(zr[m], zl[m]);
      pinu(zr);
    }
    if constexpr (i == 3) pin(z);
    if constexpr (i >= 3 && i < 3 + ZN) epi_silu<(32 * (i - 3) / ZN) & ~1, (32 * (i - 2) / ZN) & ~1>(z, zr);
    if constexpr (T == 34) { TRC(99); TRG(164); TRC(13); }
  });
  wg_wait<0>();
  TRC(137);
  pin(y);
  epi_store4<8>(P.out + orow + j * 64 + (q & 1) * 6, tt, z, y, q & 1);
  TRC(138);
  TRG(253);
  spin_check(c);
}

DEVI void main_producer(const Params& P, uint32_t sb, int mi, int j) {
  const uint32_t bar = sb + OFF_BAR;
  uint32_t c = 0;
  Ring rg = {0, 1};
  if (elect()) {
    uint32_t dst = sb, fb = bar + 8 * B_X0;
#pragma unroll 1
    for (int u = 1, kb = j, n = 1; u < 18; u++, n++) {
      if (n == 3) { n = 0; fb += 8; }
      dst += u == 9 ? 8192 - 8 * SLOT : SLOT;
      if (++kb == 9) kb = 0;
      tma_x(dst, &P.xp, fb, kb * 64, 2 * mi + (u > 8));
    }
  }
  __syncwarp();
  asm volatile("barrier.cluster.wait.acquire.aligned;" ::: "memory");
  const int rk = mi & 1;
#pragma unroll 1
  for (int t = 0; t < 10; t++) {
    const CUtensorMap* m0 = t == 1 ? &P.bre : &P.wg;
    int kb = j;
#pragma unroll 1
    for (int u = 0; u < 9; u++) {
      const int c0 = t == 1 ? kb * 64 : j * DM + (t ? t - 1 : 0) * 64, c1 = t == 1 ? j * 64 : kb * 64;
      PWAIT(c, bar + 8 * B_EMPTY + rg.o, rg.ph);
      if (elect()) {
        const uint32_t fb = bar + 8 * B_FULL + rg.o, dst = sb + 9 * SLOT + rg.o * 2048;
        mbar_expect(fb, SLOT); tma2d_mc(dst + rk * 8192, m0 + rk, fb, c0, c1);
      }
      TR(2, 9 * t + u);
      if (++kb == 9) kb = 0;
      ring_next(rg);
    }
  }
#pragma unroll 1
  for (int b = 0; b < 9; b++) {
    const int c0 = blk_of(j, b) * 64;
    sfor<0, 3>([&](auto I) {
      constexpr int i = I.v;
      const int T = 4 * b + i + (i && b == 8 ? NC1 : 0), U = T & 7;
      const uint32_t fb = bar + 8 * (B_FULLT + U), dst = sb + SLOT + U * UNIT + rk * (UNIT / 2);
      if (b > 1) mbar_wait(c, bar + 8 * (B_EMPTYT + U), ((T >> 3) - 1) & 1);
      else if (i == 2 - 2 * b) {
        mbar_wait(c, bar + 8 * (B_EMPTY + 1 + b), 1);
        mbar_arrive_warp(bar + 8 * (b ? B_P2 : B_FULL));
        if (b) { mbar_wait(c, bar + 8 * (B_EMPTY + 4), 1); mbar_arrive_warp(bar + 8 * (B_P2 + 1)); mbar_arrive_warp(bar + 8 * B_DF); mbar_arrive_warp(bar + 8 * (B_DF + 1)); }
      }
      if (elect()) { mbar_expect(fb, UNIT); tma2d_mc(dst, &P.wd, fb, c0, j * DM + i * 192 + rk * 96); }
      TR(2, 100 + T);
    });
  }
  spin_check(c);
}
DEVI void spare_producer(const Params& P, uint32_t sb, int sp, int wg, int lane, uint32_t ep) {
  const uint32_t bar = sb + OFF_BAR, rb = bar + 40 * wg, dst = sb + 9 * SLOT + wg * 8192;
  uint32_t c = 0;
  if (wg == 0 && elect()) {
    mbar_expect(bar + 8 * B_RES, 9 * SLOT);
#pragma unroll 1
    for (int u = 0; u < 18; u++) tma2d(sb + u * 8192, &P.bre + (u & 1), bar + 8 * B_RES, (u >> 1) * 64, 512);
  }
  Ring rg = {0, 1};
#pragma unroll 1
  for (int r = 0; r < 4; r++) {
    const int seg = 8 * r + 4 * wg + sp;
    if (r < 2) poll_ge(&g_sync[SY_XN + ((8 * (r ? lane & 3 : 0) + 4 * wg + sp) >> 1) * 32], ep * 8);
    __syncwarp();
#pragma unroll 1
    for (int u = 0; u < 9; u++) {
      mbar_wait(c, rb + 8 * B_EMPTY + rg.o, rg.ph);
      if (elect()) {
        const uint32_t fb = rb + 8 * B_FULL + rg.o;
        mbar_expect(fb, 8192);
        bulk_ld(dst + rg.o * 2048, g_xn + ((seg >> 1) * 9 + u) * 1024 + (seg & 1) * 512, 8192, fb);
      }
      ring_next(rg);
    }
  }
  if (!wg) {
#pragma unroll 1
    for (int k = lane >> 1; k < 144; k += 16) pf_l2(P.pw[5 + (lane & 1)] + (512 + 16 * sp) * DM + k * 64);
  } else {
    rg.o = 0; rg.ph = 1;
#pragma unroll 1
    for (int u = 0; u < 21; u++) {
      if (!(u & 15) || u == 20) poll_ge(&g_sync[(u == 20 ? SY_Z : SY_HS) + (4 * (lane & 7) + sp) * 32 + (u >> 4)], u == 16 ? ep : ep * 8);
      __syncwarp();
      if (!u) mbar_wait(c, bar + 8 * B_XN, 0);
      mbar_wait(c, bar + 8 * (B_XN + 1) + rg.o, rg.ph);
      if (elect()) {
        const uint32_t fb = bar + 8 * B_XT + rg.o, st = sb + rg.o * 9216;
        mbar_expect(fb, u < 18 ? 9 * 8192 : 8 * 8192);
        if (u < 18) { tma2d(st + 65536, &P.cre + (u & 1), fb, (u >> 1) * 64, 512); tma2d(st + 69632, &P.cre + (u & 1), fb, (u >> 1) * 64, 544); }
#pragma unroll 1
        for (int k = 0; k < 8; k++) {
          const int seg = 4 * k + sp;
          if (u < 18) tma2d(st + k * 8192, &P.hs, fb, seg * 64, (9 * (u & 1) + (u >> 1)) * 64);
          else if (u == 19) tma_x(st + k * 8192, &P.xp, fb, 512, seg);
          else bulk_ld(st + k * 8192, (u == 18 ? g_xn : g_z) + ((seg >> 1) * 9 + 8) * 1024 + (seg & 1) * 512, 8192, fb);
        }
      }
      rg.o += 8; if (rg.o == 24) { rg.o = 0; rg.ph ^= 1; }
    }
  }
  spin_check(c);
}
DEVI void pf72(const __nv_bfloat16* p, int stride, int lane, int n, int pause) {
  p += (lane >> 1) * stride;
#pragma unroll 1
  for (int k = lane; k < n; k += 24, p += 12 * stride) {
    pf_l2(p);
    asm volatile("nanosleep.u32 %0;" :: "r"(pause));
  }
}
DEVI void main_helper(const Params& P, uint32_t sb, int mi, int j, int lane, uint32_t ep) {
  const uint32_t bar = sb + OFF_BAR;
  uint32_t c = 0;
  mbar_wait_h(c, bar + 8 * (B_X0 + 2), 0);
  if (lane < 24) {
    if (!(EPF & 2)) pf72(P.pw[lane & 1] + 36 * mi * FF + j * DM, FF, lane, 72, 0);
    else if (lane == 0 && mi < 8) asm volatile("cp.async.bulk.prefetch.tensor.2d.L2.global [%0, {%1, %2}];" :: "l"(&P.wg + (mi & 1)), "r"(j * DM), "r"((j + 5 + (mi >> 1)) % 9 * 64) : "memory");
  } else if (lane < 30) asm volatile("prefetch.tensormap [%0];" :: "l"(&P.wd + lane - 24) : "memory");
  __syncwarp();
  mbar_wait_h(c, bar + 8 * (B_X0 + 5), 0);
  if (EPF & 1) {
    if (elect()) asm volatile("cp.async.bulk.prefetch.L2.global [%0], 4608;\ncp.async.bulk.prefetch.L2.global [%1], 4608;" :: "l"(P.pw[3] + (j * 64 + mi * 4) * DM), "l"(P.pw[4] + (j * 64 + mi * 4) * DM) : "memory");
  } else if (lane < 24) pf72(P.pw[3 + (lane & 1)] + (j * 64 + mi * 4) * DM, 64, lane, 72, 0);
  __syncwarp();
  TR(2, 244);
  mbar_wait_h(c, bar + 8 * B_XN, 0);
  TR(2, 245);
  if (elect()) {
    fence_async_smem();
#pragma unroll 1
    for (int k = 0, n = j == 7 ? 4096 : 2048; k < 8 * n; k += n) { bulk_st(g_xn + (mi * 9 + j) * 1024 + k / 16, sb + k, n); asm volatile("nanosleep.u32 100;"); }
    asm volatile("cp.async.bulk.commit_group;\ncp.async.bulk.wait_group 0;" ::: "memory");
    fence_gpu();
    TR(2, 246);
    red_inc(&g_sync[SY_XN + mi * 32]);
  }
  __syncwarp();
  if (elect()) {
#pragma unroll 1
    for (int n = mi; n < 144; n += 16) {
      const int t = n * 57 >> 10;
      asm volatile("cp.async.bulk.prefetch.tensor.2d.L2.global [%0, {%1, %2}];" :: "l"(&P.wg + (n & 1)), "r"(j * DM + 64 + t * 64), "r"((n - 18 * t >> 1) * 64) : "memory");
      if (n >= 16) asm volatile("nanosleep.u32 %0;\nnanosleep.u32 %1;" :: "n"(PFP), "n"(BPF));
    }
#pragma unroll 1
    for (int n = 0; n < 11; n++) {
      asm volatile("cp.async.bulk.prefetch.L2.global [%0], 4608;" :: "l"(n < 9 ? P.pw[2] + (j * DM + 36 * mi + 4 * n) * DM : P.pw[n - 4] + (j * 64 + mi * 4) * DM) : "memory");
      asm volatile("nanosleep.u32 %0;" :: "n"(PFP));
    }
  }
  __syncwarp();
  TR(2, 248);
#pragma unroll 1
  for (int n = 0; n < 18; n++) {
    const int T = n < 8 ? 4 * n + 3 : n + (n < 8 + NC1 ? 25 : 27), U = T & 7;
    const uint32_t fb = bar + 8 * (B_FULLT + U), dst = sb + SLOT + U * UNIT;
    if (n == 0 || n == 4) {
      if (lane < 2) poll_ge(&g_sync[SY_HS + (2 * mi + lane) * 32 + (n >> 2)], n ? ep : ep * 8);
      __syncwarp();
      TR(2, 249);
      mbar_arrive_warp_if(bar + 8 * B_G1, !n);
    }
    mbar_wait_h(c, n < 2 ? bar + 8 * (B_P2 + n) : bar + 8 * (B_EMPTYT + U), n < 2 ? 0 : ((T >> 3) - 1) & 1);
    if (elect()) {
      mbar_expect(fb, UNIT);
      tma2d_mc(dst + SLOT + (mi & 1) * 4096, &P.cre + (n > 8), fb, (n > 8 ? n - 9 : n) * 64, j * 64 + (mi & 1) * 32);
      asm volatile("cp.async.bulk.tensor.3d.shared::cluster.global.mbarrier::complete_tx::bytes [%0], [%1, {%3, %4, %5}], [%2];"
                   :: "r"(dst), "l"(&P.hs2), "r"(fb), "r"(0), "r"(n * 64), "r"(2 * mi) : "memory");
    }
    TR(2, 100 + T);
  }
  spin_check(c);
}
DEVI void wg_helper(const Params& P, uint32_t sb, int wg, int mi, int j, int lane, uint32_t ep) {
  const uint32_t bar = sb + OFF_BAR + 8 * wg;
  const bool mainc = blockIdx.x < 128;
  const int seg0 = mainc ? 2 * mi + wg : blockIdx.x - 128 + 4 * wg, nr = mainc ? 1 : 4;
  uint32_t c = 0;
  if (mainc) {
    mbar_wait_h(c, sb + OFF_BAR + 8 * ZW, 0);
    if (ZS) asm volatile("nanosleep.u32 %0;" :: "n"(ZS));
    uint4* zp = g_z + (mi * 9 + j) * 1024 + wg * 512 + lane;
    uint4* z7 = g_z7 + (mi * 8 + j) * 1024 + wg * 512 + lane;
#pragma unroll 1
    for (int k = 0; k < 16; k++) {
      zp[k * 32] = make_uint4(0, 0, 0, 0); if (Z32) z7[k * 32].x = ~0u; else z7[k * 32] = make_uint4(~0u, ~0u, ~0u, ~0u);
      if (k < 2) g_z[(mi * 9 + 8) * 1024 + j * 128 + wg * 64 + k * 32 + lane] = make_uint4(0, 0, 0, 0);
      asm volatile("nanosleep.u32 %0;" :: "n"(ZP));
    }
    __syncwarp();
  }
#pragma unroll 1
  for (int r = 0; r < nr; r++) {
    const int seg = seg0 + 8 * r;
    mbar_wait_h(c, bar + 8 * B_HS, r & 1);
    TR(2, 223 + 12 * wg);
    if (lane == 0) { fence_async_all(); fence_gpu(); red_inc(&g_sync[SY_HS + seg * 32 + !mainc]); }
    __syncwarp();
    TR(2, 224 + 12 * wg);
  }
  if (mainc) {
    mbar_wait_h(c, sb + OFF_BAR + 8 * B_G1, 0);
    const uint32_t stg = sb + 13 * SLOT + wg * 8192;
#pragma unroll 1
    for (int b = 0; b < 7; b++) {
      mbar_wait_h(c, bar + 8 * B_DR, b & 1);
      TR(2, 225 + 12 * wg);
      if (elect()) {
        fence_async_smem();
        bulk_red(g_z + (mi * 9 + blk_of(j, b)) * 1024 + wg * 512, stg, 8192);
        asm volatile("cp.async.bulk.commit_group;\ncp.async.bulk.wait_group.read 0;" ::: "memory");
        mbar_arrive(bar + 8 * B_DF);
        TR(2, 226 + 12 * wg);
        if (b == 0) { mbar_expect(bar + 8 * B_XT, 8192); tma_x(sb + wg * 8192, &P.xp, bar + 8 * B_XT, j * 64, seg0); }
        if (b == 3 || b == 6) {
          asm volatile("cp.async.bulk.wait_group 0;" ::: "memory");
          fence_gpu();
          TR(2, 227 + 12 * wg);
          red_inc(&g_sync[SY_Z + seg0 * 32 + (b == 3)]);
        }
        if (b == 6) {
          mbar_expect(bar + 8 * B_Z, 8192);
          poll_ge(&g_sync[SY_Z + seg0 * 32], ep * 8);
          TR(2, 229 + 12 * wg);
          bulk_ld(stg, g_z + (mi * 9 + j) * 1024 + wg * 512, 8192, bar + 8 * B_Z);
        }
      }
      __syncwarp();
    }
  }
  if (wg == 1 && lane == 0) st_relaxed(&g_sync[SY_EPOCH + blockIdx.x], ep);
  spin_check(c);
}

__global__ void __cluster_dims__(2, 1, 1) __launch_bounds__(384, 1) fused_kernel(const __grid_constant__ Params P) {
  extern __shared__ __align__(1024) uint8_t smem_raw[];
  uint32_t sb = smem_u32(smem_raw);
  asm volatile("" : "+r"(sb));
  const int bid = blockIdx.x, j = CJ(bid), mi = CM(bid);
  const int warp = __shfl_sync(0xffffffffu, threadIdx.x >> 5, 0), lane = threadIdx.x & 31;
  if (warp < 8) {
    TRC(255); TRG(254);
    const int ch = j * 64 + 16 * (warp & 3) + (lane >> 2) + 8 * (lane & 1);
    const __nv_bfloat16 p_re = P.lre[ch], p_im = P.lim[ch], p_dt = P.ldt[ch];
    const uint32_t p_d = *(const uint32_t*)(P.dskip + j * 64 + 2 * lane);
    if (elect()) {
      const uint32_t cnt = (warp & 4) ? (warp == 7 || bid >= 128 ? 4 : 16) : 1;
#pragma unroll
      for (int k = 0; k < 6; k++) mbar_init(sb + OFF_BAR + 48 * warp + 8 * k, k && warp == 6 ? 8 : cnt);
      asm volatile("fence.mbarrier_init.release.cluster;" ::: "memory");
    }
    TR(2, 200 + warp);
    __syncwarp();
    asm volatile("barrier.cluster.arrive.relaxed.aligned;\nbar.sync 0, 384;" ::: "memory");
    TRC(141);
    asm volatile("st.shared.b32 [%0], %1;" :: "r"(sb + OFF_D + (lane & 3) * 32 + (lane & 28)), "r"(p_d) : "memory");
    scan_params(sb + OFF_PAR + (ch & 63) * 16, __bfloat162float(p_re), __bfloat162float(p_im), __bfloat162float(p_dt));
    TRC(142);
    asm volatile("setmaxnreg.inc.sync.aligned.u32 240;");
    TRC(143);
    if (bid >= 128) spare_consumer(P, sb, warp, lane); else main_consumer(P, sb, warp >> 2, mi, j);
    tr_dump();
  } else {
    if (warp != 8) {
      if (EPF & 8) { if (bid < 128 && threadIdx.x == 288) asm volatile("cp.async.bulk.prefetch.L2.global [%0], 9216;" :: "l"(P.x + (mi * 128 + j * 8) * DM) : "memory"); } else
      if (bid < 128 && threadIdx.x < 360) pf_l2(P.x + (mi * 128 + j * 8) * DM + (threadIdx.x - 288) * 64);
    } else {
      if (elect()) {
#pragma unroll
        for (int k = 0; k < 6; k++) mbar_init(sb + OFF_BAR + 8 * (B_X0 + k), 1);
        asm volatile("fence.mbarrier_init.release.cluster;" ::: "memory");
        if (bid < 128) {
          mbar_expect(sb + OFF_BAR + 8 * B_X0, 3 * 8192);
          tma_x(sb, &P.xp, sb + OFF_BAR + 8 * B_X0, j * 64, mi * 2);
#pragma unroll
          for (int k = 1; k < 6; k++) mbar_expect(sb + OFF_BAR + 8 * (B_X0 + k), 3 * 8192);
          asm volatile("prefetch.tensormap [%0];\nprefetch.tensormap [%1];" :: "l"(&P.wg), "l"(&P.wu) : "memory");
        }
      }
      __syncwarp();
    }
    TR(2, 200 + warp);
    asm volatile("barrier.cluster.arrive.relaxed.aligned;\nsetmaxnreg.dec.sync.aligned.u32 24;" ::: "memory");
    if (warp != 8 || bid >= 128) {
      asm volatile("bar.sync 0, 384;" ::: "memory");
      if (PFX && bid < 128) {
        const int t = threadIdx.x - 288;
        if (t < 72) {
          if (!(EPF & 4)) pf_l2(P.x + (mi * 128 + 64 + j * 8) * DM + t * 64);
          else if (t == 0) asm volatile("cp.async.bulk.prefetch.L2.global [%0], 9216;" :: "l"(P.x + (mi * 128 + 64 + j * 8) * DM) : "memory");
        }
        else if (PFX != 2 && t < 80) pf_l2(P.pw[t & 1] + (j * 64 + mi * 4 + ((t >> 1) & 3)) * FF + j * DM);
      }
      const uint32_t ep = ld_epoch();
      if (warp < 10 && bid >= 128) spare_producer(P, sb, bid - 128, warp - 8, lane, ep);
      else if (warp >= 10) wg_helper(P, sb, warp - 10, mi, j, lane, ep);
      else main_helper(P, sb, mi, j, lane, ep);
    } else {
      asm volatile("bar.arrive 0, 384;" ::: "memory");
      main_producer(P, sb, mi, j);
    }
  }
}
typedef CUresult (*EncodeFn)(CUtensorMap*, CUtensorMapDataType, cuuint32_t, void*, const cuuint64_t*, const cuuint64_t*, const cuuint32_t*,
                             const cuuint32_t*, CUtensorMapInterleave, CUtensorMapSwizzle, CUtensorMapL2promotion, CUtensorMapFloatOOBfill);
static void make_map(EncodeFn enc, CUtensorMap* m, const void* ptr, int rank, const cuuint64_t* dims, const cuuint64_t* strides, const cuuint32_t* box) {
  const cuuint32_t es[5] = {1, 1, 1, 1, 1};
  enc(m, CU_TENSOR_MAP_DATA_TYPE_BFLOAT16, rank, (void*)ptr, dims, strides, box, es, CU_TENSOR_MAP_INTERLEAVE_NONE,
      CU_TENSOR_MAP_SWIZZLE_128B, CU_TENSOR_MAP_L2_PROMOTION_L2_128B, CU_TENSOR_MAP_FLOAT_OOB_FILL_NONE);
}
static void map2d(EncodeFn enc, CUtensorMap* m, const void* ptr, uint64_t inner, uint64_t outer, cuuint32_t rows = 64) {
  const cuuint64_t dims[2] = {inner, outer}, strides[1] = {inner * 2};
  const cuuint32_t box[2] = {64, rows};
  make_map(enc, m, ptr, 2, dims, strides, box);
}

extern "C" void kernel_launch(void* const* d_in, const int* in_sizes, int n_in, void* d_out, int out_size) {
  void* fn = nullptr;
  cudaDriverEntryPointQueryResult st;
  cudaGetDriverEntryPoint("cuTensorMapEncodeTiled", &fn, cudaEnableDefault, &st);
  EncodeFn enc = (EncodeFn)fn;
  void* hs = nullptr;
  cudaGetSymbolAddress(&hs, g_hsT);
  Params P;
  map2d(enc, &P.wg, d_in[10], FF, DM); map2d(enc, &P.wu, d_in[11], FF, DM); map2d(enc, &P.wd, d_in[12], DM, FF, 96);
  map2d(enc, &P.bre, d_in[3], DM, DM); map2d(enc, &P.bim, d_in[4], DM, DM);
  map2d(enc, &P.cre, d_in[5], DM, DM, 32); map2d(enc, &P.cim, d_in[6], DM, DM, 32);
  map2d(enc, &P.hs, hs, SEQ, 2 * DM);
  {
    const cuuint64_t dims[3] = {64, 2 * DM, SEQ / 64}, strides[2] = {SEQ * 2, 128};
    const cuuint32_t box[3] = {64, 64, 2};
    make_map(enc, &P.hs2, hs, 3, dims, strides, box);
  }
  {
    const cuuint64_t dims[5] = {DM, 2, 4, 8, 32}, strides[4] = {DM * 2, 16 * DM * 2, 2 * DM * 2, 64 * DM * 2};
    const cuuint32_t box[5] = {64, 2, 4, 8, 1};
    make_map(enc, &P.xp, d_in[0], 5, dims, strides, box);
  }
  P.x = (const __nv_bfloat16*)d_in[0]; P.lre = (const __nv_bfloat16*)d_in[1]; P.lim = (const __nv_bfloat16*)d_in[2];
  P.ldt = (const __nv_bfloat16*)d_in[7]; P.dskip = (const __nv_bfloat16*)d_in[8];
  const int pi[7] = {10, 11, 12, 3, 4, 5, 6};
  for (int i = 0; i < 7; i++) P.pw[i] = (const __nv_bfloat16*)d_in[pi[i]];
  P.out = (float*)d_out;
  P.desc = DESC0;
  cudaFuncSetAttribute(fused_kernel, cudaFuncAttributeMaxDynamicSharedMemorySize, SMEM_BYTES);
  fused_kernel<<<132, 384, SMEM_BYTES, cudaStreamPerThread>>>(P);
}
```
